```python
import torch

def _softmax(x, axis=-1):
    return torch.softmax(x, dim=axis)
def _gelu(x):
    return torch.nn.functional.gelu(x, approximate="tanh")
def _silu(x):
    return torch.nn.functional.silu(x)
def _sigmoid(x):
    return torch.sigmoid(x)
def _layernorm(x, axis=-1, eps=1e-5):
    m = x.mean(dim=axis, keepdim=True)
    v = x.var(dim=axis, keepdim=True, unbiased=False)
    return (x - m) / torch.sqrt(v + eps)
def _scatter_add(tgt, idx, src, axis=0):
    return tgt.clone().index_add_(axis, idx, src)
def _segment_sum(src, seg, n):
    out = torch.zeros((n,) + src.shape[1:], dtype=src.dtype)
    return out.index_add_(0, seg, src)
def _pad(x, pw):
    flat = tuple(v for pair in reversed(pw) for v in pair)
    return torch.nn.functional.pad(x, flat)

kernel_name = 'parallel_sum__ssm_conv_s4__mixer_token_mlp__prompt'

def setup_inputs():

    _w = (lambda a: (lambda t: t.to(torch.bfloat16) if t.is_floating_point() else t)(torch.as_tensor(a)))
    def _A_setup():
        B, L, D, N = 1, 2048, 640, 128
        A_re = -(lambda _x: torch.exp(torch.as_tensor(_x)))((lambda *s: torch.randn(*s, dtype=torch.bfloat16) * 3.2)(D, N))
        A_im = torch.pi * (lambda *s: torch.randn(*s, dtype=torch.bfloat16) * 0.05)(D, N)
        B_re = (lambda *s: torch.randn(*s, dtype=torch.bfloat16) * 0.1)(D, N)
        B_im = (lambda *s: torch.randn(*s, dtype=torch.bfloat16) * 0.1)(D, N)
        C_re = (lambda *s: torch.randn(*s, dtype=torch.bfloat16) * 0.1)(D, N)
        C_im = (lambda *s: torch.randn(*s, dtype=torch.bfloat16) * 0.1)(D, N)
        log_dt = (lambda *s: torch.randn(*s, dtype=torch.bfloat16) * 0.05)(D) * 0.5 - 4.0
        Dskip = (lambda *s: torch.randn(*s, dtype=torch.bfloat16) * 0.05)(D)
        return {
            "u": _w((lambda *s: torch.randn(*s, dtype=torch.bfloat16) * 0.05)(B, L, D)),
            "A_re": _w(A_re),
            "A_im": _w(A_im),
            "B_re": _w(B_re),
            "B_im": _w(B_im),
            "C_re": _w(C_re),
            "C_im": _w(C_im),
            "log_dt": _w(log_dt),
            "Dskip": _w(Dskip),
        }
    _A_in = _A_setup()

    def _B_setup():
        B, S, D, F = 1, 2048, 640, 1728
        return {
            "x": _w((lambda *s: torch.randn(*s, dtype=torch.bfloat16) * 0.05)(B, S, D)),
            "w1": _w((lambda *s: torch.randn(*s, dtype=torch.bfloat16) * 0.8)(S, F) * (S ** -0.5)),
            "b1": _w((lambda *s: torch.randn(*s, dtype=torch.bfloat16) * 3.2)(F) * 0.02),
            "w2": _w((lambda *s: torch.randn(*s, dtype=torch.bfloat16) * 0.8)(F, S) * (F ** -0.5)),
            "b2": _w((lambda *s: torch.randn(*s, dtype=torch.bfloat16) * 3.2)(S) * 0.02),
        }
    _B_in = _B_setup()

    return {
        "A_u": _A_in["u"],
        "A_A_re": _A_in["A_re"],
        "A_A_im": _A_in["A_im"],
        "A_B_re": _A_in["B_re"],
        "A_B_im": _A_in["B_im"],
        "A_C_re": _A_in["C_re"],
        "A_C_im": _A_in["C_im"],
        "A_log_dt": _A_in["log_dt"],
        "A_Dskip": _A_in["Dskip"],
        "B_x": _B_in["x"],
        "B_w1": _B_in["w1"],
        "B_b1": _B_in["b1"],
        "B_w2": _B_in["w2"],
        "B_b2": _B_in["b2"],
    }

def reference(A_u, A_A_re, A_A_im, A_B_re, A_B_im, A_C_re, A_C_im, A_log_dt, A_Dskip, B_x, B_w1, B_b1, B_w2, B_b2):
    def _A_ref(u, A_re, A_im, B_re, B_im, C_re, C_im, log_dt, Dskip):
        Bsz, L, D = u.shape
        dt = torch.exp(log_dt)[:, None]
        A = A_re + 1j * A_im
        Bc = B_re + 1j * B_im
        Cc = C_re + 1j * C_im
        logdA = dt * A
        dB = dt * Bc
        l = (lambda x, dt: x.to(dt))(torch.arange(L), A_re.dtype)
        P = torch.exp(logdA[:, :, None] * l[None, None, :])
        K = torch.einsum("dn,dnl,dn->dl", Cc, P, dB).real
        L2 = 2 * L
        Kp = _pad(K, ((0, 0), (0, L)))
        up = (lambda x, *d: x.permute(*d))(u, 0, 2, 1)
        up = _pad(up, ((0, 0), (0, 0), (0, L)))
        Kf = (lambda x, axes=(-2,-1): torch.fft.rfft2(x.float(), dim=axes))(Kp[:, None, :], axes=(-2, -1))
        Uf = (lambda x, axes=(-2,-1): torch.fft.rfft2(x.float(), dim=axes))(up[:, :, None, :], axes=(-2, -1))
        Yf = Uf * Kf[None, :, :, :]
        y = (lambda x, s, axes=(-2,-1): torch.fft.irfft2(x, s=s, dim=axes).to(torch.bfloat16))(Yf, (1, L2), axes=(-2, -1))[:, :, 0, :L]
        y = (lambda x, *d: x.permute(*d))(y, 0, 2, 1) + u * Dskip[None, None, :]
        return y

    def _B_ref(x, w1, b1, w2, b2):
        B, S, D = x.shape
        h = _layernorm(x, axis=-1)
        u = torch.einsum("bsd,sf->bdf", h, w1) + b1
        u = _gelu(u)
        y = torch.einsum("bdf,fs->bds", u, w2) + b2
        return (lambda x, *d: x.permute(*d))(y, 0, 2, 1)

    x = A_u
    xn = _layernorm(x, axis=-1)
    return x + _A_ref(xn, A_A_re, A_A_im, A_B_re, A_B_im, A_C_re, A_C_im, A_log_dt, A_Dskip) + _B_ref(xn, B_w1, B_b1, B_w2, B_b2)
```

```cpp
#include <cuda_runtime.h>
#include <cuda_bf16.h>
#include <cuda.h>
#include <stdint.h>
#include <stdlib.h>

namespace {

constexpr int S_ = 2048, D_ = 640, F_ = 1728, NM_ = 128;
constexpr int NCTA = 132;
constexpr int NTHREADS = 512;
constexpr int STAGES = 6;
constexpr int SA = 8192, SB = 20480;
constexpr int KB1 = S_ / 64, KB2 = F_ / 64;

constexpr int IMG_B2 = 0;
constexpr int IMG_B3 = 1536;
constexpr int IMG_P = 3584;
constexpr int TB_T = 0, TB_T2 = 784, TB_T3 = 1200, TB_SIZE = 1648, T2P = 48, T3P = 96,
              T_G1024 = 386, T_ZERO = 387;
constexpr int CV_ZERO = 0, CV_IMG = 1536, CV_U = CV_IMG + 5952, CV_R2 = CV_U + 4224, CV_R3 = CV_R2 + 7776, CV_TAB = 22528, CV_SIZE = 24192;
constexpr int U_PLANE = 2112, U_SIZE = 2 * U_PLANE;
constexpr int SM_A = 0, SM_B = STAGES * SA, SM_CV = SM_B + STAGES * SB, SM_UX = SM_CV + 2 * CV_SIZE, SM_TABX = SM_UX + 2 * U_SIZE,
              SM_BAR = SM_TABX + 2 * TB_SIZE;
constexpr int SMEM_BYTES = SM_BAR + 288;
constexpr int SM_LNST = SM_B + 5 * SB, SM_LNX = SM_B + 4 * SB;
constexpr int SM_FU = SM_B, SM_FTAB = SM_B + 12 * U_SIZE, SM_FST = SM_B + 70656,
              SM_FSD = SM_A + 32768;
static_assert(SMEM_BYTES <= 232448, "smem");
constexpr int B_FULL = 0, B_EMPTY = 6, B_EPIY = 12, B_CVFREE = 13, B_EPOCH = 14, B_LNST = 15, B_LNG = 17  ,
              B_LNALL = 19, B_LNDONE = 20, B_GST = 21, B_UIN = 22, B_BFREE = 23, B_NONE = 24, B_KGDONE = 25, B_STG = 26, B_SYNC = 27, B_KGMMA = 16, B_YOK = 30, B_YFREE = 31  , B_WORD = 28;
constexpr int KG_REC = 176;
static_assert(128 * KG_REC <= CV_TAB, "k-gen scratch");
constexpr int C_LN = 0, C_G = 128, C_CONV = 256, C_EPOCH = 288;
constexpr unsigned N_LN = 32, N_G = 128;

__device__ __align__(1024) __nv_bfloat16 g_hT[D_ * S_];
__device__ __align__(1024) __nv_bfloat16 g_st[2 * S_];
__device__ __align__(1024) __nv_bfloat16 g_yT[D_ * S_];
__device__ __align__(1024) __nv_bfloat16 g_G[D_ * F_];
__device__ __align__(1024) unsigned g_cnt[352];
#define TR(i)
#define TRP(c, i)

struct Params {
  __nv_bfloat16* out;
  const __nv_bfloat16 *x, *are, *aim, *bre, *bim, *cre, *cim, *logdt, *dskip, *b1, *b2;
  int phases;
  int use_smid;
  int dbg, uat, uat2;
};

__device__ __forceinline__ uint64_t gtime() { uint64_t t; asm volatile("mov.u64 %0, %%globaltimer;" : "=l"(t)); return t; }
__device__ __forceinline__ uint32_t smem_u32(const void* p) { return (uint32_t)__cvta_generic_to_shared(p); }
__device__ __forceinline__ void mbar_init(uint32_t bar, uint32_t cnt) { asm volatile("mbarrier.init.shared::cta.b64 [%0], %1;" ::"r"(bar), "r"(cnt) : "memory"); }
__device__ __forceinline__ void mbar_expect_tx(uint32_t bar, uint32_t bytes) { asm volatile("mbarrier.arrive.expect_tx.shared::cta.b64 _, [%0], %1;" ::"r"(bar), "r"(bytes) : "memory"); }
[[maybe_unused]] __device__ __forceinline__ void mbar_expect_only(uint32_t bar, uint32_t bytes) { asm volatile("mbarrier.expect_tx.relaxed.cta.shared::cta.b64 [%0], %1;" ::"r"(bar), "r"(bytes) : "memory"); }
__device__ __forceinline__ void mbar_arrive(uint32_t bar) { asm volatile("mbarrier.arrive.shared::cta.b64 _, [%0];" ::"r"(bar) : "memory"); }
__device__ __forceinline__ void mbar_arrive_n(uint32_t bar, uint32_t n) { asm volatile("mbarrier.arrive.shared::cta.b64 _, [%0], %1;" ::"r"(bar), "r"(n) : "memory"); }
__device__ __forceinline__ bool mbar_try(uint32_t bar, uint32_t parity) {
  uint32_t ok;
  asm volatile("{ .reg .pred p; mbarrier.try_wait.parity.shared::cta.b64 p, [%1], %2; selp.u32 %0,1,0,p; }" : "=r"(ok) : "r"(bar), "r"(parity) : "memory");
  return ok;
}
__device__ __forceinline__ bool mbar_test(uint32_t bar, uint32_t parity) {
  uint32_t ok;
  asm volatile("{ .reg .pred p; mbarrier.test_wait.parity.shared::cta.b64 p, [%1], %2; selp.u32 %0,1,0,p; }" : "=r"(ok) : "r"(bar), "r"(parity) : "memory");
  return ok;
}
__device__ __forceinline__ void mbar_wait(uint32_t bar, uint32_t parity) {
#pragma unroll 1
  for (int i = 0; i < (1 << 20); i++) { if (mbar_try(bar, parity)) return; }
  __trap();
}
__device__ __forceinline__ void tma_load(uint32_t dst, const CUtensorMap* m, int c0, int c1, uint32_t bar) {
  asm volatile("cp.async.bulk.tensor.2d.shared::cluster.global.mbarrier::complete_tx::bytes [%0], [%1, {%3,%4}], [%2];" ::"r"(dst), "l"(m), "r"(bar), "r"(c0), "r"(c1) : "memory");
}
__device__ __forceinline__ void tma_load3(uint32_t dst, const CUtensorMap* m, int c0, int c1, int c2, uint32_t bar) {
  asm volatile("cp.async.bulk.tensor.3d.shared::cluster.global.mbarrier::complete_tx::bytes [%0], [%1, {%3,%4,%5}], [%2];" ::"r"(dst), "l"(m), "r"(bar), "r"(c0), "r"(c1), "r"(c2) : "memory");
}
__device__ __forceinline__ void tma_store(const CUtensorMap* m, int c0, int c1, uint32_t src) {
  asm volatile("cp.async.bulk.tensor.2d.global.shared::cta.bulk_group [%0, {%2,%3}], [%1];" ::"l"(m), "r"(src), "r"(c0), "r"(c1) : "memory");
}
__device__ __forceinline__ void tma_prefetch(const CUtensorMap* m, int c0, int c1) {
  asm volatile("cp.async.bulk.prefetch.tensor.2d.L2.global [%0, {%1,%2}];" ::"l"(m), "r"(c0), "r"(c1) : "memory");
}
__device__ __forceinline__ void bulk_load(uint32_t dst, const void* src, uint32_t bytes, uint32_t bar) {
  asm volatile("cp.async.bulk.shared::cluster.global.mbarrier::complete_tx::bytes [%0], [%1], %2, [%3];" ::"r"(dst), "l"(src), "r"(bytes), "r"(bar) : "memory");
}
__device__ __forceinline__ void bulk_store(void* dst, uint32_t src, uint32_t bytes) {
  asm volatile("cp.async.bulk.global.shared::cta.bulk_group [%0], [%1], %2;" ::"l"(dst), "r"(src), "r"(bytes) : "memory");
}
__device__ __forceinline__ void bulk_commit() { asm volatile("cp.async.bulk.commit_group;" ::: "memory"); }
__device__ __forceinline__ void bulk_wait_all() { asm volatile("cp.async.bulk.wait_group 0;" ::: "memory"); }
__device__ __forceinline__ void bulk_wait_read() { asm volatile("cp.async.bulk.wait_group.read 0;" ::: "memory"); }
__device__ __forceinline__ void fence_async_smem() { asm volatile("fence.proxy.async.shared::cta;" ::: "memory"); }
__device__ __forceinline__ void fence_async_all() { asm volatile("fence.proxy.async;" ::: "memory"); }
__device__ __forceinline__ bool elect() {
  uint32_t p;
  asm volatile("{ .reg .pred p; elect.sync _|p, 0xffffffff; selp.u32 %0, 1, 0, p; }" : "=r"(p));
  return p;
}
__device__ __forceinline__ void named_arrive(int id, int n) { asm volatile("bar.arrive %0, %1;" ::"r"(id), "r"(n) : "memory"); }
__device__ __forceinline__ void named_bar(int id, int n) { asm volatile("bar.sync %0, %1;" ::"r"(id), "r"(n) : "memory"); }
[[maybe_unused]] __device__ __forceinline__ void cnt_arrive(unsigned* p) { asm volatile("red.release.gpu.global.add.u32 [%0], 1;" ::"l"(p) : "memory"); }
__device__ __forceinline__ void cnt_arrive_done(unsigned* p) { asm volatile("red.relaxed.gpu.global.add.u32 [%0], 1;" ::"l"(p) : "memory"); }
__device__ __forceinline__ unsigned cnt_ld(const unsigned* p) {
  unsigned val;
  asm volatile("ld.relaxed.gpu.global.u32 %0, [%1];" : "=r"(val) : "l"(p) : "memory");
  return val;
}
__device__ __forceinline__ void cnt_wait(const unsigned* p, unsigned target) {
#pragma unroll 1
  for (int i = 0; i < (1 << 20); i++)
    if ((int)(cnt_ld(p) - target) >= 0) return;
  __trap();
}
__device__ __forceinline__ void cnt_arrive_timed(unsigned* p, unsigned delay) {
  asm volatile("red.relaxed.gpu.global.max.u64 [%0], %1;" ::"l"(p + 2), "l"(gtime() + delay) : "memory");
  cnt_arrive_done(p);
}
__device__ __forceinline__ void cnt_wait_timed(const unsigned* p, unsigned target) {
  uint64_t c, t;
#pragma unroll 1
  for (int i = 0;; i++) {
    asm volatile("ld.relaxed.gpu.global.v2.u64 {%0,%1}, [%2];" : "=l"(c), "=l"(t) : "l"(p) : "memory");
    if ((int)((unsigned)c - target) >= 0) break;
    if (i > (1 << 20)) __trap();
  }
#pragma unroll 1
  for (int i = 0; i < 256 && gtime() < t; i++) {}
}
__device__ __forceinline__ void wg_fence() { asm volatile("wgmma.fence.sync.aligned;" ::: "memory"); }
__device__ __forceinline__ void wg_commit() { asm volatile("wgmma.commit_group.sync.aligned;" ::: "memory"); }
template <int N> __device__ __forceinline__ void wg_wait() { asm volatile("wgmma.wait_group.sync.aligned %0;" ::"n"(N) : "memory"); }
[[maybe_unused]] __device__ __forceinline__ uint64_t mkdesc(uint32_t addr, uint32_t lbo, uint32_t sbo, uint32_t sw) {
  return (uint64_t)((addr & 0x3FFFF) >> 4) | ((uint64_t)(lbo >> 4) << 16) | ((uint64_t)(sbo >> 4) << 32) | ((uint64_t)sw << 62);
}
[[maybe_unused]] __device__ __forceinline__ void ldsm4(uint32_t* r, uint32_t a) {
  asm volatile("ldmatrix.sync.aligned.m8n8.x4.shared.b16 {%0,%1,%2,%3}, [%4];" : "=r"(r[0]), "=r"(r[1]), "=r"(r[2]), "=r"(r[3]) : "r"(a) : "memory");
}
__device__ __forceinline__ void ldsm4t(uint32_t* r, uint32_t a) {
  asm volatile("ldmatrix.sync.aligned.m8n8.x4.trans.shared.b16 {%0,%1,%2,%3}, [%4];" : "=r"(r[0]), "=r"(r[1]), "=r"(r[2]), "=r"(r[3]) : "r"(a) : "memory");
}
__device__ __forceinline__ void ldsm2t(uint32_t* r, uint32_t a) {
  asm volatile("ldmatrix.sync.aligned.m8n8.x2.trans.shared.b16 {%0,%1}, [%2];" : "=r"(r[0]), "=r"(r[1]) : "r"(a) : "memory");
}
[[maybe_unused]] __device__ __forceinline__ void stsm4(uint32_t a, uint32_t r0, uint32_t r1, uint32_t r2, uint32_t r3) {
  asm volatile("stmatrix.sync.aligned.m8n8.x4.shared.b16 [%0], {%1,%2,%3,%4};" ::"r"(a), "r"(r0), "r"(r1), "r"(r2), "r"(r3) : "memory");
}
__device__ __forceinline__ void stsm4t(uint32_t a, uint32_t r0, uint32_t r1, uint32_t r2, uint32_t r3) {
  asm volatile("stmatrix.sync.aligned.m8n8.x4.trans.shared.b16 [%0], {%1,%2,%3,%4};" ::"r"(a), "r"(r0), "r"(r1), "r"(r2), "r"(r3) : "memory");
}
__device__ __forceinline__ void mma16816(float* c, const uint32_t* a, uint32_t b0, uint32_t b1) {
  asm volatile("mma.sync.aligned.m16n8k16.row.col.f32.bf16.bf16.f32 {%0,%1,%2,%3}, {%4,%5,%6,%7}, {%8,%9}, {%0,%1,%2,%3};"
               : "+f"(c[0]), "+f"(c[1]), "+f"(c[2]), "+f"(c[3]) : "r"(a[0]), "r"(a[1]), "r"(a[2]), "r"(a[3]), "r"(b0), "r"(b1));
}
__device__ __forceinline__ void sts128(uint32_t a, uint32_t x, uint32_t y, uint32_t z, uint32_t w) {
  asm volatile("st.shared.v4.b32 [%0], {%1,%2,%3,%4};" ::"r"(a), "r"(x), "r"(y), "r"(z), "r"(w) : "memory");
}
__device__ __forceinline__ void sts32(uint32_t a, uint32_t x) { asm volatile("st.shared.b32 [%0], %1;" ::"r"(a), "r"(x) : "memory"); }
__device__ __forceinline__ void sts16(uint32_t a, uint16_t x) { asm volatile("st.shared.b16 [%0], %1;" ::"r"(a), "h"(x) : "memory"); }
__device__ __forceinline__ uint4 lds128(uint32_t a) {
  uint4 r; asm volatile("ld.shared.v4.b32 {%0,%1,%2,%3}, [%4];" : "=r"(r.x), "=r"(r.y), "=r"(r.z), "=r"(r.w) : "r"(a) : "memory"); return r;
}
__device__ __forceinline__ uint2 lds64(uint32_t a) {
  uint2 r; asm volatile("ld.shared.v2.b32 {%0,%1}, [%2];" : "=r"(r.x), "=r"(r.y) : "r"(a) : "memory"); return r;
}
__device__ __forceinline__ uint32_t lds32(uint32_t a) { uint32_t r; asm volatile("ld.shared.b32 %0, [%1];" : "=r"(r) : "r"(a) : "memory"); return r; }
__device__ __forceinline__ uint32_t lds16(uint32_t a) { uint16_t r; asm volatile("ld.shared.b16 %0, [%1];" : "=h"(r) : "r"(a) : "memory"); return r; }
__device__ __forceinline__ uint4 ldg128(const void* p) {
  uint4 r; asm volatile("ld.global.v4.b32 {%0,%1,%2,%3}, [%4];" : "=r"(r.x), "=r"(r.y), "=r"(r.z), "=r"(r.w) : "l"(p) : "memory"); return r;
}
__device__ __forceinline__ uint32_t pk(float lo, float hi) { uint32_t r; asm("cvt.rn.bf16x2.f32 %0, %1, %2;" : "=r"(r) : "f"(hi), "f"(lo)); return r; }
__device__ __forceinline__ float blo(uint32_t x) { return __uint_as_float(x << 16); }
__device__ __forceinline__ float bhi(uint32_t x) { return __uint_as_float(x & 0xffff0000u); }
__device__ __forceinline__ float bf16r(float x) { return __bfloat162float(__float2bfloat16_rn(x)); }
__device__ __forceinline__ uint32_t hadd2(uint32_t a, uint32_t b) { uint32_t r; asm("add.rn.bf16x2 %0, %1, %2;" : "=r"(r) : "r"(a), "r"(b)); return r; }
__device__ __forceinline__ uint32_t hfma2(uint32_t a, uint32_t b, uint32_t c) { uint32_t r; asm("fma.rn.bf16x2 %0, %1, %2, %3;" : "=r"(r) : "r"(a), "r"(b), "r"(c)); return r; }
__device__ __forceinline__ int perm(int n) { return (n & ~30) | ((n & 6) << 2) | ((n >> 2) & 6); }
__device__ __forceinline__ float ldbf(const __nv_bfloat16* p) { return __bfloat162float(__ldg(p)); }

template <uint32_t HA, uint32_t HB> __device__ __forceinline__ void wg_gemm160(float* d, uint32_t da, uint32_t db, int sc) {
  asm volatile("{ .reg .pred p; .reg .b64 a, b; setp.ne.b32 p, %84, 0; mov.b64 a, {%80, %82}; mov.b64 b, {%81, %83}; wgmma.mma_async.sync.aligned.m64n160k16.f32.bf16.bf16 {%0,%1,%2,%3,%4,%5,%6,%7,%8,%9,%10,%11,%12,%13,%14,%15,%16,%17,%18,%19,%20,%21,%22,%23,%24,%25,%26,%27,%28,%29,%30,%31,%32,%33,%34,%35,%36,%37,%38,%39,%40,%41,%42,%43,%44,%45,%46,%47,%48,%49,%50,%51,%52,%53,%54,%55,%56,%57,%58,%59,%60,%61,%62,%63,%64,%65,%66,%67,%68,%69,%70,%71,%72,%73,%74,%75,%76,%77,%78,%79}, a, b, p, 1, 1, 1, 0; }"
    : "+f"(d[0]),"+f"(d[1]),"+f"(d[2]),"+f"(d[3]),"+f"(d[4]),"+f"(d[5]),"+f"(d[6]),"+f"(d[7]),"+f"(d[8]),"+f"(d[9]),"+f"(d[10]),"+f"(d[11]),"+f"(d[12]),"+f"(d[13]),"+f"(d[14]),"+f"(d[15]),"+f"(d[16]),"+f"(d[17]),"+f"(d[18]),"+f"(d[19]),"+f"(d[20]),"+f"(d[21]),"+f"(d[22]),"+f"(d[23]),"+f"(d[24]),"+f"(d[25]),"+f"(d[26]),"+f"(d[27]),"+f"(d[28]),"+f"(d[29]),"+f"(d[30]),"+f"(d[31]),"+f"(d[32]),"+f"(d[33]),"+f"(d[34]),"+f"(d[35]),"+f"(d[36]),"+f"(d[37]),"+f"(d[38]),"+f"(d[39]),"+f"(d[40]),"+f"(d[41]),"+f"(d[42]),"+f"(d[43]),"+f"(d[44]),"+f"(d[45]),"+f"(d[46]),"+f"(d[47]),"+f"(d[48]),"+f"(d[49]),"+f"(d[50]),"+f"(d[51]),"+f"(d[52]),"+f"(d[53]),"+f"(d[54]),"+f"(d[55]),"+f"(d[56]),"+f"(d[57]),"+f"(d[58]),"+f"(d[59]),"+f"(d[60]),"+f"(d[61]),"+f"(d[62]),"+f"(d[63]),"+f"(d[64]),"+f"(d[65]),"+f"(d[66]),"+f"(d[67]),"+f"(d[68]),"+f"(d[69]),"+f"(d[70]),"+f"(d[71]),"+f"(d[72]),"+f"(d[73]),"+f"(d[74]),"+f"(d[75]),"+f"(d[76]),"+f"(d[77]),"+f"(d[78]),"+f"(d[79]) : "r"(da), "r"(db), "n"(HA), "n"(HB), "r"(sc));
}
template <uint32_t HA, uint32_t HB> __device__ __forceinline__ void wg_win96(float* d, uint32_t da, uint32_t db) {
  asm volatile("{ .reg .b64 a, b; mov.b64 a, {%48, %50}; mov.b64 b, {%49, %51}; wgmma.mma_async.sync.aligned.m64n96k16.f32.bf16.bf16 {%0,%1,%2,%3,%4,%5,%6,%7,%8,%9,%10,%11,%12,%13,%14,%15,%16,%17,%18,%19,%20,%21,%22,%23,%24,%25,%26,%27,%28,%29,%30,%31,%32,%33,%34,%35,%36,%37,%38,%39,%40,%41,%42,%43,%44,%45,%46,%47}, a, b, 1, 1, 1, 1, 1; }"
    : "+f"(d[0]),"+f"(d[1]),"+f"(d[2]),"+f"(d[3]),"+f"(d[4]),"+f"(d[5]),"+f"(d[6]),"+f"(d[7]),"+f"(d[8]),"+f"(d[9]),"+f"(d[10]),"+f"(d[11]),"+f"(d[12]),"+f"(d[13]),"+f"(d[14]),"+f"(d[15]),"+f"(d[16]),"+f"(d[17]),"+f"(d[18]),"+f"(d[19]),"+f"(d[20]),"+f"(d[21]),"+f"(d[22]),"+f"(d[23]),"+f"(d[24]),"+f"(d[25]),"+f"(d[26]),"+f"(d[27]),"+f"(d[28]),"+f"(d[29]),"+f"(d[30]),"+f"(d[31]),"+f"(d[32]),"+f"(d[33]),"+f"(d[34]),"+f"(d[35]),"+f"(d[36]),"+f"(d[37]),"+f"(d[38]),"+f"(d[39]),"+f"(d[40]),"+f"(d[41]),"+f"(d[42]),"+f"(d[43]),"+f"(d[44]),"+f"(d[45]),"+f"(d[46]),"+f"(d[47]) : "r"(da), "r"(db), "n"(HA), "n"(HB));
}
template <uint32_t HA, uint32_t HB> __device__ __forceinline__ void wg_win80(float* d, uint32_t da, uint32_t db) {
  asm volatile("{ .reg .b64 a, b; mov.b64 a, {%40, %42}; mov.b64 b, {%41, %43}; wgmma.mma_async.sync.aligned.m64n80k16.f32.bf16.bf16 {%0,%1,%2,%3,%4,%5,%6,%7,%8,%9,%10,%11,%12,%13,%14,%15,%16,%17,%18,%19,%20,%21,%22,%23,%24,%25,%26,%27,%28,%29,%30,%31,%32,%33,%34,%35,%36,%37,%38,%39}, a, b, 1, 1, 1, 1, 1; }"
    : "+f"(d[0]),"+f"(d[1]),"+f"(d[2]),"+f"(d[3]),"+f"(d[4]),"+f"(d[5]),"+f"(d[6]),"+f"(d[7]),"+f"(d[8]),"+f"(d[9]),"+f"(d[10]),"+f"(d[11]),"+f"(d[12]),"+f"(d[13]),"+f"(d[14]),"+f"(d[15]),"+f"(d[16]),"+f"(d[17]),"+f"(d[18]),"+f"(d[19]),"+f"(d[20]),"+f"(d[21]),"+f"(d[22]),"+f"(d[23]),"+f"(d[24]),"+f"(d[25]),"+f"(d[26]),"+f"(d[27]),"+f"(d[28]),"+f"(d[29]),"+f"(d[30]),"+f"(d[31]),"+f"(d[32]),"+f"(d[33]),"+f"(d[34]),"+f"(d[35]),"+f"(d[36]),"+f"(d[37]),"+f"(d[38]),"+f"(d[39]) : "r"(da), "r"(db), "n"(HA), "n"(HB));
}
template <uint32_t HA, uint32_t HB> __device__ __forceinline__ void wg_win64(float* d, uint32_t da, uint32_t db) {
  asm volatile("{ .reg .b64 a, b; mov.b64 a, {%32, %34}; mov.b64 b, {%33, %35}; wgmma.mma_async.sync.aligned.m64n64k16.f32.bf16.bf16 {%0,%1,%2,%3,%4,%5,%6,%7,%8,%9,%10,%11,%12,%13,%14,%15,%16,%17,%18,%19,%20,%21,%22,%23,%24,%25,%26,%27,%28,%29,%30,%31}, a, b, 1, 1, 1, 1, 1; }"
    : "+f"(d[0]),"+f"(d[1]),"+f"(d[2]),"+f"(d[3]),"+f"(d[4]),"+f"(d[5]),"+f"(d[6]),"+f"(d[7]),"+f"(d[8]),"+f"(d[9]),"+f"(d[10]),"+f"(d[11]),"+f"(d[12]),"+f"(d[13]),"+f"(d[14]),"+f"(d[15]),"+f"(d[16]),"+f"(d[17]),"+f"(d[18]),"+f"(d[19]),"+f"(d[20]),"+f"(d[21]),"+f"(d[22]),"+f"(d[23]),"+f"(d[24]),"+f"(d[25]),"+f"(d[26]),"+f"(d[27]),"+f"(d[28]),"+f"(d[29]),"+f"(d[30]),"+f"(d[31]) : "r"(da), "r"(db), "n"(HA), "n"(HB));
}
template <uint32_t HA, uint32_t HB> __device__ __forceinline__ void wg_win48(float* d, uint32_t da, uint32_t db) {
  asm volatile("{ .reg .b64 a, b; mov.b64 a, {%24, %26}; mov.b64 b, {%25, %27}; wgmma.mma_async.sync.aligned.m64n48k16.f32.bf16.bf16 {%0,%1,%2,%3,%4,%5,%6,%7,%8,%9,%10,%11,%12,%13,%14,%15,%16,%17,%18,%19,%20,%21,%22,%23}, a, b, 1, 1, 1, 1, 1; }"
    : "+f"(d[0]),"+f"(d[1]),"+f"(d[2]),"+f"(d[3]),"+f"(d[4]),"+f"(d[5]),"+f"(d[6]),"+f"(d[7]),"+f"(d[8]),"+f"(d[9]),"+f"(d[10]),"+f"(d[11]),"+f"(d[12]),"+f"(d[13]),"+f"(d[14]),"+f"(d[15]),"+f"(d[16]),"+f"(d[17]),"+f"(d[18]),"+f"(d[19]),"+f"(d[20]),"+f"(d[21]),"+f"(d[22]),"+f"(d[23]) : "r"(da), "r"(db), "n"(HA), "n"(HB));
}
template <uint32_t HA, uint32_t HB> __device__ __forceinline__ void wg_win32(float* d, uint32_t da, uint32_t db) {
  asm volatile("{ .reg .b64 a, b; mov.b64 a, {%16, %18}; mov.b64 b, {%17, %19}; wgmma.mma_async.sync.aligned.m64n32k16.f32.bf16.bf16 {%0,%1,%2,%3,%4,%5,%6,%7,%8,%9,%10,%11,%12,%13,%14,%15}, a, b, 1, 1, 1, 1, 1; }"
    : "+f"(d[0]),"+f"(d[1]),"+f"(d[2]),"+f"(d[3]),"+f"(d[4]),"+f"(d[5]),"+f"(d[6]),"+f"(d[7]),"+f"(d[8]),"+f"(d[9]),"+f"(d[10]),"+f"(d[11]),"+f"(d[12]),"+f"(d[13]),"+f"(d[14]),"+f"(d[15]) : "r"(da), "r"(db), "n"(HA), "n"(HB));
}
template <uint32_t HA, uint32_t HB> __device__ __forceinline__ void wg_win16(float* d, uint32_t da, uint32_t db) {
  asm volatile("{ .reg .b64 a, b; mov.b64 a, {%8, %10}; mov.b64 b, {%9, %11}; wgmma.mma_async.sync.aligned.m64n16k16.f32.bf16.bf16 {%0,%1,%2,%3,%4,%5,%6,%7}, a, b, 1, 1, 1, 1, 1; }"
    : "+f"(d[0]),"+f"(d[1]),"+f"(d[2]),"+f"(d[3]),"+f"(d[4]),"+f"(d[5]),"+f"(d[6]),"+f"(d[7]) : "r"(da), "r"(db), "n"(HA), "n"(HB));
}
template <uint32_t HB, int SC> __device__ __forceinline__ void wg_dir128(float* d, const uint32_t* a, uint32_t db) {
  asm volatile("{ .reg .b64 b; mov.b64 b, {%68, %69}; wgmma.mma_async.sync.aligned.m64n128k16.f32.bf16.bf16 {%0,%1,%2,%3,%4,%5,%6,%7,%8,%9,%10,%11,%12,%13,%14,%15,%16,%17,%18,%19,%20,%21,%22,%23,%24,%25,%26,%27,%28,%29,%30,%31,%32,%33,%34,%35,%36,%37,%38,%39,%40,%41,%42,%43,%44,%45,%46,%47,%48,%49,%50,%51,%52,%53,%54,%55,%56,%57,%58,%59,%60,%61,%62,%63}, {%64,%65,%66,%67}, b, %70, 1, 1, 0; }"
    : "+f"(d[0]),"+f"(d[1]),"+f"(d[2]),"+f"(d[3]),"+f"(d[4]),"+f"(d[5]),"+f"(d[6]),"+f"(d[7]),"+f"(d[8]),"+f"(d[9]),"+f"(d[10]),"+f"(d[11]),"+f"(d[12]),"+f"(d[13]),"+f"(d[14]),"+f"(d[15]),"+f"(d[16]),"+f"(d[17]),"+f"(d[18]),"+f"(d[19]),"+f"(d[20]),"+f"(d[21]),"+f"(d[22]),"+f"(d[23]),"+f"(d[24]),"+f"(d[25]),"+f"(d[26]),"+f"(d[27]),"+f"(d[28]),"+f"(d[29]),"+f"(d[30]),"+f"(d[31]),"+f"(d[32]),"+f"(d[33]),"+f"(d[34]),"+f"(d[35]),"+f"(d[36]),"+f"(d[37]),"+f"(d[38]),"+f"(d[39]),"+f"(d[40]),"+f"(d[41]),"+f"(d[42]),"+f"(d[43]),"+f"(d[44]),"+f"(d[45]),"+f"(d[46]),"+f"(d[47]),"+f"(d[48]),"+f"(d[49]),"+f"(d[50]),"+f"(d[51]),"+f"(d[52]),"+f"(d[53]),"+f"(d[54]),"+f"(d[55]),"+f"(d[56]),"+f"(d[57]),"+f"(d[58]),"+f"(d[59]),"+f"(d[60]),"+f"(d[61]),"+f"(d[62]),"+f"(d[63]) : "r"(a[0]), "r"(a[1]), "r"(a[2]), "r"(a[3]), "r"(db), "n"(HB), "n"(SC));
}
template <uint32_t HB, int SC> __device__ __forceinline__ void wg_dir120(float* d, const uint32_t* a, uint32_t db) {
  asm volatile("{ .reg .b64 b; mov.b64 b, {%64, %65}; wgmma.mma_async.sync.aligned.m64n120k16.f32.bf16.bf16 {%0,%1,%2,%3,%4,%5,%6,%7,%8,%9,%10,%11,%12,%13,%14,%15,%16,%17,%18,%19,%20,%21,%22,%23,%24,%25,%26,%27,%28,%29,%30,%31,%32,%33,%34,%35,%36,%37,%38,%39,%40,%41,%42,%43,%44,%45,%46,%47,%48,%49,%50,%51,%52,%53,%54,%55,%56,%57,%58,%59}, {%60,%61,%62,%63}, b, %66, 1, 1, 0; }"
    : "+f"(d[0]),"+f"(d[1]),"+f"(d[2]),"+f"(d[3]),"+f"(d[4]),"+f"(d[5]),"+f"(d[6]),"+f"(d[7]),"+f"(d[8]),"+f"(d[9]),"+f"(d[10]),"+f"(d[11]),"+f"(d[12]),"+f"(d[13]),"+f"(d[14]),"+f"(d[15]),"+f"(d[16]),"+f"(d[17]),"+f"(d[18]),"+f"(d[19]),"+f"(d[20]),"+f"(d[21]),"+f"(d[22]),"+f"(d[23]),"+f"(d[24]),"+f"(d[25]),"+f"(d[26]),"+f"(d[27]),"+f"(d[28]),"+f"(d[29]),"+f"(d[30]),"+f"(d[31]),"+f"(d[32]),"+f"(d[33]),"+f"(d[34]),"+f"(d[35]),"+f"(d[36]),"+f"(d[37]),"+f"(d[38]),"+f"(d[39]),"+f"(d[40]),"+f"(d[41]),"+f"(d[42]),"+f"(d[43]),"+f"(d[44]),"+f"(d[45]),"+f"(d[46]),"+f"(d[47]),"+f"(d[48]),"+f"(d[49]),"+f"(d[50]),"+f"(d[51]),"+f"(d[52]),"+f"(d[53]),"+f"(d[54]),"+f"(d[55]),"+f"(d[56]),"+f"(d[57]),"+f"(d[58]),"+f"(d[59]) : "r"(a[0]), "r"(a[1]), "r"(a[2]), "r"(a[3]), "r"(db), "n"(HB), "n"(SC));
}
template <uint32_t HB, int SC> __device__ __forceinline__ void wg_dir112(float* d, const uint32_t* a, uint32_t db) {
  asm volatile("{ .reg .b64 b; mov.b64 b, {%60, %61}; wgmma.mma_async.sync.aligned.m64n112k16.f32.bf16.bf16 {%0,%1,%2,%3,%4,%5,%6,%7,%8,%9,%10,%11,%12,%13,%14,%15,%16,%17,%18,%19,%20,%21,%22,%23,%24,%25,%26,%27,%28,%29,%30,%31,%32,%33,%34,%35,%36,%37,%38,%39,%40,%41,%42,%43,%44,%45,%46,%47,%48,%49,%50,%51,%52,%53,%54,%55}, {%56,%57,%58,%59}, b, %62, 1, 1, 0; }"
    : "+f"(d[0]),"+f"(d[1]),"+f"(d[2]),"+f"(d[3]),"+f"(d[4]),"+f"(d[5]),"+f"(d[6]),"+f"(d[7]),"+f"(d[8]),"+f"(d[9]),"+f"(d[10]),"+f"(d[11]),"+f"(d[12]),"+f"(d[13]),"+f"(d[14]),"+f"(d[15]),"+f"(d[16]),"+f"(d[17]),"+f"(d[18]),"+f"(d[19]),"+f"(d[20]),"+f"(d[21]),"+f"(d[22]),"+f"(d[23]),"+f"(d[24]),"+f"(d[25]),"+f"(d[26]),"+f"(d[27]),"+f"(d[28]),"+f"(d[29]),"+f"(d[30]),"+f"(d[31]),"+f"(d[32]),"+f"(d[33]),"+f"(d[34]),"+f"(d[35]),"+f"(d[36]),"+f"(d[37]),"+f"(d[38]),"+f"(d[39]),"+f"(d[40]),"+f"(d[41]),"+f"(d[42]),"+f"(d[43]),"+f"(d[44]),"+f"(d[45]),"+f"(d[46]),"+f"(d[47]),"+f"(d[48]),"+f"(d[49]),"+f"(d[50]),"+f"(d[51]),"+f"(d[52]),"+f"(d[53]),"+f"(d[54]),"+f"(d[55]) : "r"(a[0]), "r"(a[1]), "r"(a[2]), "r"(a[3]), "r"(db), "n"(HB), "n"(SC));
}
template <uint32_t HB, int SC> __device__ __forceinline__ void wg_dir104(float* d, const uint32_t* a, uint32_t db) {
  asm volatile("{ .reg .b64 b; mov.b64 b, {%56, %57}; wgmma.mma_async.sync.aligned.m64n104k16.f32.bf16.bf16 {%0,%1,%2,%3,%4,%5,%6,%7,%8,%9,%10,%11,%12,%13,%14,%15,%16,%17,%18,%19,%20,%21,%22,%23,%24,%25,%26,%27,%28,%29,%30,%31,%32,%33,%34,%35,%36,%37,%38,%39,%40,%41,%42,%43,%44,%45,%46,%47,%48,%49,%50,%51}, {%52,%53,%54,%55}, b, %58, 1, 1, 0; }"
    : "+f"(d[0]),"+f"(d[1]),"+f"(d[2]),"+f"(d[3]),"+f"(d[4]),"+f"(d[5]),"+f"(d[6]),"+f"(d[7]),"+f"(d[8]),"+f"(d[9]),"+f"(d[10]),"+f"(d[11]),"+f"(d[12]),"+f"(d[13]),"+f"(d[14]),"+f"(d[15]),"+f"(d[16]),"+f"(d[17]),"+f"(d[18]),"+f"(d[19]),"+f"(d[20]),"+f"(d[21]),"+f"(d[22]),"+f"(d[23]),"+f"(d[24]),"+f"(d[25]),"+f"(d[26]),"+f"(d[27]),"+f"(d[28]),"+f"(d[29]),"+f"(d[30]),"+f"(d[31]),"+f"(d[32]),"+f"(d[33]),"+f"(d[34]),"+f"(d[35]),"+f"(d[36]),"+f"(d[37]),"+f"(d[38]),"+f"(d[39]),"+f"(d[40]),"+f"(d[41]),"+f"(d[42]),"+f"(d[43]),"+f"(d[44]),"+f"(d[45]),"+f"(d[46]),"+f"(d[47]),"+f"(d[48]),"+f"(d[49]),"+f"(d[50]),"+f"(d[51]) : "r"(a[0]), "r"(a[1]), "r"(a[2]), "r"(a[3]), "r"(db), "n"(HB), "n"(SC));
}
template <uint32_t HB, int SC> __device__ __forceinline__ void wg_dir96(float* d, const uint32_t* a, uint32_t db) {
  asm volatile("{ .reg .b64 b; mov.b64 b, {%52, %53}; wgmma.mma_async.sync.aligned.m64n96k16.f32.bf16.bf16 {%0,%1,%2,%3,%4,%5,%6,%7,%8,%9,%10,%11,%12,%13,%14,%15,%16,%17,%18,%19,%20,%21,%22,%23,%24,%25,%26,%27,%28,%29,%30,%31,%32,%33,%34,%35,%36,%37,%38,%39,%40,%41,%42,%43,%44,%45,%46,%47}, {%48,%49,%50,%51}, b, %54, 1, 1, 0; }"
    : "+f"(d[0]),"+f"(d[1]),"+f"(d[2]),"+f"(d[3]),"+f"(d[4]),"+f"(d[5]),"+f"(d[6]),"+f"(d[7]),"+f"(d[8]),"+f"(d[9]),"+f"(d[10]),"+f"(d[11]),"+f"(d[12]),"+f"(d[13]),"+f"(d[14]),"+f"(d[15]),"+f"(d[16]),"+f"(d[17]),"+f"(d[18]),"+f"(d[19]),"+f"(d[20]),"+f"(d[21]),"+f"(d[22]),"+f"(d[23]),"+f"(d[24]),"+f"(d[25]),"+f"(d[26]),"+f"(d[27]),"+f"(d[28]),"+f"(d[29]),"+f"(d[30]),"+f"(d[31]),"+f"(d[32]),"+f"(d[33]),"+f"(d[34]),"+f"(d[35]),"+f"(d[36]),"+f"(d[37]),"+f"(d[38]),"+f"(d[39]),"+f"(d[40]),"+f"(d[41]),"+f"(d[42]),"+f"(d[43]),"+f"(d[44]),"+f"(d[45]),"+f"(d[46]),"+f"(d[47]) : "r"(a[0]), "r"(a[1]), "r"(a[2]), "r"(a[3]), "r"(db), "n"(HB), "n"(SC));
}
template <uint32_t HB, int SC> __device__ __forceinline__ void wg_dir64(float* d, const uint32_t* a, uint32_t db) {
  asm volatile("{ .reg .b64 b; mov.b64 b, {%36, %37}; wgmma.mma_async.sync.aligned.m64n64k16.f32.bf16.bf16 {%0,%1,%2,%3,%4,%5,%6,%7,%8,%9,%10,%11,%12,%13,%14,%15,%16,%17,%18,%19,%20,%21,%22,%23,%24,%25,%26,%27,%28,%29,%30,%31}, {%32,%33,%34,%35}, b, %38, 1, 1, 0; }"
    : "+f"(d[0]),"+f"(d[1]),"+f"(d[2]),"+f"(d[3]),"+f"(d[4]),"+f"(d[5]),"+f"(d[6]),"+f"(d[7]),"+f"(d[8]),"+f"(d[9]),"+f"(d[10]),"+f"(d[11]),"+f"(d[12]),"+f"(d[13]),"+f"(d[14]),"+f"(d[15]),"+f"(d[16]),"+f"(d[17]),"+f"(d[18]),"+f"(d[19]),"+f"(d[20]),"+f"(d[21]),"+f"(d[22]),"+f"(d[23]),"+f"(d[24]),"+f"(d[25]),"+f"(d[26]),"+f"(d[27]),"+f"(d[28]),"+f"(d[29]),"+f"(d[30]),"+f"(d[31]) : "r"(a[0]), "r"(a[1]), "r"(a[2]), "r"(a[3]), "r"(db), "n"(HB), "n"(SC));
}

struct cf { float r, i; };
__device__ __forceinline__ cf cmul(cf a, cf b) { return cf{fmaf(a.r, b.r, -a.i * b.i), fmaf(a.r, b.i, a.i * b.r)}; }
__device__ __forceinline__ cf cexp_at(float lr, float pt, float x) {
  float m, s, c;
  asm("ex2.approx.ftz.f32 %0, %1;" : "=f"(m) : "f"(lr * x));
  float t = pt * x;
  t = (t - rintf(t)) * 6.283185307179586f;
  asm("sin.approx.ftz.f32 %0, %1;" : "=f"(s) : "f"(t));
  asm("cos.approx.ftz.f32 %0, %1;" : "=f"(c) : "f"(t));
  return cf{m * c, m * s};
}
__device__ __forceinline__ cf cmulc(cf a, cf b) { return cf{fmaf(a.r, b.r, a.i * b.i), fmaf(a.i, b.r, -a.r * b.i)}; }
__device__ __forceinline__ int lag_index(int x) {
  int b = (int)(pk((float)x, 0.f) & 0xffffu) - 0x4300 + 128;
  int r = x < 128 ? x : b;
  return x >= 515 ? T_ZERO : r;
}

struct KgIn { uint2 are, aim, bre, bim, cre, cim; uint32_t logdt, dskip; };
__device__ __forceinline__ uint32_t ldraw(const __nv_bfloat16* p) { uint32_t r; asm volatile("ld.global.nc.u16 %0, [%1];" : "=r"(r) : "l"(p)); return r; }
__device__ __forceinline__ uint2 ldraw4(const __nv_bfloat16* p) { uint2 r; asm volatile("ld.global.nc.v2.u32 {%0,%1}, [%2];" : "=r"(r.x), "=r"(r.y) : "l"(p)); return r; }
__device__ __forceinline__ KgIn kg_load(const Params& p, int n, int lane) {
  KgIn k;
  const int d = perm(n), o = d * NM_ + 4 * lane;
  k.are = ldraw4(p.are + o); k.aim = ldraw4(p.aim + o); k.bre = ldraw4(p.bre + o); k.bim = ldraw4(p.bim + o);
  k.cre = ldraw4(p.cre + o); k.cim = ldraw4(p.cim + o);
  k.logdt = ldraw(p.logdt + d); k.dskip = ldraw(p.dskip + d);
  return k;
}
__device__ __forceinline__ float next4(uint2& x) {
  const float r = blo(x.x);
  x.x = __byte_perm(x.x, x.y, 0x5432); x.y >>= 16;
  return r;
}

__device__ __forceinline__ void kgen_channel(KgIn in, int lane, uint32_t sm, uint32_t tab, int r0, int r1, uint32_t xs, uint32_t shared) {
  if (r0 == 0) {
#pragma unroll
    for (int i = 0; i < 4; i++)
      if (i * 32 + lane < TB_SIZE / 16) sts128(tab + (i * 32 + lane) * 16, 0u, 0u, 0u, 0u);
  }
  if (r0 >= 2) { in.are.x = in.are.y; in.aim.x = in.aim.y; in.bre.x = in.bre.y; in.bim.x = in.bim.y; in.cre.x = in.cre.y; in.cim.x = in.cim.y; }
  float dt;
  asm("ex2.approx.ftz.f32 %0, %1;" : "=f"(dt) : "f"(blo(in.logdt) * 1.4426950408889634f));
  dt = bf16r(dt);
  const uint32_t rec = sm + lane * KG_REC;
  const int mat = lane >> 3, rho = lane & 7;
  const uint32_t baddr = sm + (4 * (mat & 1) + (rho >> 1)) * KG_REC + 32 + (rho & 1) * 64 + (mat >> 1) * 16;
  const uint32_t baddr2 = sm + (4 * (mat & 1) + (rho >> 1)) * KG_REC + 128 + (rho & 1) * 16;
  const uint32_t aaddr = sm + (4 * (mat >> 1) + (rho >> 1)) * KG_REC + (rho & 1) * 64 + (mat & 1) * 16;
  float acc[2][3][4];
#pragma unroll
  for (int mt = 0; mt < 2; mt++)
#pragma unroll
    for (int nt = 0; nt < 3; nt++)
#pragma unroll
      for (int e = 0; e < 4; e++) acc[mt][nt][e] = 0.f;
#pragma unroll 1
  for (int r = r0; r < r1; r++) {
    const float lr = (dt * next4(in.are)) * 1.4426950408889634f;
    const float pt = (dt * next4(in.aim)) * 0.15915494309189535f;
    const cf e1 = cexp_at(lr, pt, 1.f), e8 = cexp_at(lr, pt, 8.f), e256 = cexp_at(lr, pt, 256.f);
    {
      const float cr = next4(in.cre), ci = next4(in.cim), br = next4(in.bre), bi = next4(in.bim);
      const cf c = cmulc(cf{cr, -ci}, cf{dt * br, dt * bi});
      const cf e2 = cmul(e1, e1), e4 = cmul(e2, e2);
      cf w0 = c, w1 = cmulc(c, e1), w2 = cmulc(c, e2), w3 = cmulc(w1, e2);
      cf w4 = cmulc(w0, e4), w5 = cmulc(w1, e4), w6 = cmulc(w2, e4), w7 = cmulc(w3, e4);
      __syncwarp();
      sts128(rec + 32, pk(w0.r, w1.r), pk(w2.r, w3.r), pk(w4.r, w5.r), pk(w6.r, w7.r));
      sts128(rec + 96, pk(w0.i, w1.i), pk(w2.i, w3.i), pk(w4.i, w5.i), pk(w6.i, w7.i));
      const cf e512 = cmul(e256, e256);
      w0 = cmulc(w0, e256); w2 = cmulc(w2, e256); w1 = cmulc(w4, e256); w3 = cmulc(w6, e256);
      w5 = cmulc(w4, e512); w4 = cmulc(c, e512);
      w6 = cmulc(w0, e512); w7 = cmulc(w1, e512);
      sts128(rec + 48, pk(w0.r, w2.r), pk(w1.r, w3.r), pk(w4.r, w5.r), pk(w6.r, w7.r));
      sts128(rec + 112, pk(w0.i, w2.i), pk(w1.i, w3.i), pk(w4.i, w5.i), pk(w6.i, w7.i));
      w0 = cmulc(w4, e512); w1 = cmulc(w6, e512); w2 = cmulc(w0, e512); w3 = cmulc(w1, e512); w4 = cmulc(w2, e512);
      sts128(rec + 128, pk(w0.r, w1.r), pk(w2.r, w3.r), pk(w4.r, 0.f), 0u);
      sts128(rec + 144, pk(w0.i, w1.i), pk(w2.i, w3.i), pk(w4.i, 0.f), 0u);
    }
    __syncwarp();
    uint32_t bf[4][6];
#pragma unroll
    for (int ks = 0; ks < 4; ks++) { ldsm4t(bf[ks], baddr + ks * 8 * KG_REC); ldsm2t(bf[ks] + 4, baddr2 + ks * 8 * KG_REC); }
    {
      cf v0{1.f, 0.f}, v1 = e8, v2 = cmul(e8, e8), v3 = cmul(v2, e8);
      const cf e32 = cmul(v2, v2);
#pragma unroll
      for (int ch = 0; ch < 4; ch++) {
        const cf n0 = ch == 0 ? e32 : cmul(v0, e32), n1 = cmul(v1, e32), n2 = cmul(v2, e32), n3 = cmul(v3, e32);
        if (ch == 2) __syncwarp();
        sts128(rec + ch * 16, pk(v0.r, v1.r), pk(v2.r, v3.r), pk(n0.r, n1.r), pk(n2.r, n3.r));
        sts128(rec + ch * 16 + 64, pk(v0.i, v1.i), pk(v2.i, v3.i), pk(n0.i, n1.i), pk(n2.i, n3.i));
        if (ch < 3) { v0 = cmul(n0, e32); v1 = cmul(n1, e32); v2 = cmul(n2, e32); v3 = cmul(n3, e32); }
      }
    }
    __syncwarp();
    uint32_t af[4][2][4];
#pragma unroll
    for (int ks = 0; ks < 4; ks++) { ldsm4t(af[ks][0], aaddr + ks * 8 * KG_REC); ldsm4t(af[ks][1], aaddr + ks * 8 * KG_REC + 32); }
#pragma unroll
    for (int ks = 0; ks < 4; ks++)
#pragma unroll
      for (int mt = 0; mt < 2; mt++)
#pragma unroll
        for (int nt = 0; nt < 3; nt++) mma16816(acc[mt][nt], af[ks][mt], bf[ks][2 * nt], bf[ks][2 * nt + 1]);
  }
  if (shared) {
    float* a = &acc[0][0][0];
    if (lane == 0) asm volatile("mbarrier.arrive.shared::cta.b64 _, [%0];" ::"r"(shared), "f"(a[0]), "f"(a[23]) : "memory");
    if (r0 > 0) {
      __syncwarp();
#pragma unroll
      for (int i = 0; i < 6; i++)
        sts128(xs + (i * 32 + lane) * 16, __float_as_uint(a[4 * i]), __float_as_uint(a[4 * i + 1]),
               __float_as_uint(a[4 * i + 2]), __float_as_uint(a[4 * i + 3]));
      named_arrive(4, 256);
      return;
    }
    named_bar(4, 256);
#pragma unroll
    for (int i = 0; i < 6; i++) {
      const uint4 x = lds128(xs + (i * 32 + lane) * 16);
      a[4 * i] += __uint_as_float(x.x); a[4 * i + 1] += __uint_as_float(x.y);
      a[4 * i + 2] += __uint_as_float(x.z); a[4 * i + 3] += __uint_as_float(x.w);
    }
  }
  if (lane == 0) acc[0][0][0] += blo(in.dskip);
  const int g = lane >> 2, q = lane & 3;
  const uint32_t T = tab + TB_T, T2 = tab + TB_T2, T3 = tab + TB_T3;
  const int i1 = 64 * (q - 2) + 2 * g, i0 = i1 - 1;
  const uint32_t a10 = q < 2 ? T + (256 + 2 * q + 4 * g) * 2 : T2 + ((i0 & 3) * T2P + 47 - (i0 >> 2)) * 2;
  const uint32_t a11 = q < 2 ? a10 + 2 : T2 + ((i1 & 3) * T2P + 47 - (i1 >> 2)) * 2;
  const int st1 = q < 2 ? 64 : -8;
  const int j0 = 64 * q + g - 1;
  const uint32_t a20 = q < 2 ? T3 + ((j0 & 1) * T3P + 63 - (j0 >> 1)) * 2 : rec + 32;
  __syncwarp();
#pragma unroll
  for (int sidx = 0; sidx < 4; sidx++) {
    const int mt = sidx >> 1, h = sidx & 1;
    sts32(T + (2 * q + 8 * g + 64 * sidx) * 2, pk(acc[mt][0][2 * h], acc[mt][0][2 * h + 1]));
    const uint32_t h1 = pk(acc[mt][1][2 * h], acc[mt][1][2 * h + 1]), h2 = pk(acc[mt][2][2 * h], acc[mt][2][2 * h + 1]);
    sts16(sidx == 0 && lane == 2 ? T + 384 * 2 : a10 + sidx * st1, (uint16_t)h1);
    sts16(a11 + sidx * st1, (uint16_t)(h1 >> 16));
    sts16(sidx == 0 && lane == 0 ? T2 + (3 * T2P + 47 - 31) * 2 : sidx == 0 && lane == 2 ? T3 + T3P * 2 : a20 - sidx * 8, (uint16_t)h2);
    sts16(a20 - sidx * 8 - (q < 2 ? 32 : 0), (uint16_t)(h2 >> 16));
    if (sidx == 0 && lane == 0) sts16(T + T_G1024 * 2, (uint16_t)h2);
  }
}

__device__ __forceinline__ uint32_t conv_u(uint32_t sb, int c) {
  return sb + ((c & 1) ? SM_UX + (c >> 1) * U_SIZE : SM_CV + (c >> 1) * CV_SIZE + CV_U);
}
__device__ __forceinline__ void conv_unnorm(const uint32_t (&src)[4], const uint32_t (&dst)[4], const uint4& sd, const uint4& mu) {
  uint4 h[4];
#pragma unroll
  for (int c = 0; c < 4; c++) h[c] = lds128(src[c]);
#pragma unroll
  for (int c = 0; c < 4; c++)
    sts128(dst[c], hfma2(h[c].x, sd.x, mu.x), hfma2(h[c].y, sd.y, mu.y), hfma2(h[c].z, sd.z, mu.z), hfma2(h[c].w, sd.w, mu.w));
}
__device__ __forceinline__ int free_chan(int grp) { return 160 * (grp / 13) + 108 + 4 * (grp % 13); }
__device__ __forceinline__ void conv_image(uint32_t tab, uint32_t cv, int t, const uint32_t (&pix)[2]) {
  const int cg = t >> 4, k = t & 15;
  uint32_t a = tab + TB_T3 + ((k >> 3) * T3P + 8 * cg + 4 * (k & 7)) * 2;
  uint2 lo = lds64(a), hi = lds64(a + 8);
  sts128(cv + CV_IMG + IMG_B3 + t * 16, lo.x, lo.y, hi.x, hi.y);
  uint32_t kv[5];
#pragma unroll
  for (int e = 0; e < 5; e++) kv[e] = lds16(tab + TB_T + ((pix[e / 3] >> (10 * (e % 3))) & 1023));
  sts128(cv + CV_IMG + IMG_P + (t + 5) * 16, kv[1] | (kv[0] << 16), kv[2] | (kv[1] << 16), kv[3] | (kv[2] << 16), kv[4] | (kv[3] << 16));
  if (t < 96) {
    a = tab + TB_T2 + ((((k >> 3) ? 0 : 2) + ((k >> 2) & 1)) * T2P + 8 * cg + 4 * (k & 3)) * 2;
    lo = lds64(a); hi = lds64(a + 8);
    sts128(cv + CV_IMG + IMG_B2 + t * 16, lo.x, lo.y, hi.x, hi.y);
  } else if (t == 96) {
    lo = lds64(tab + TB_T);
    sts128(cv + CV_IMG + IMG_P + 64, lo.x & 0xffffu, __byte_perm(lo.x, 0, 0x1032), __byte_perm(lo.x, lo.y, 0x3254), __byte_perm(lo.y, 0, 0x1032));
  }
}
__device__ __forceinline__ void conv_pix(uint32_t (&pix)[2], int t) {
  pix[0] = (lag_index(4 * t + 3) << 1) | (lag_index(4 * t + 4) << 11) | (lag_index(4 * t + 5) << 21);
  pix[1] = (lag_index(4 * t + 6) << 1) | (lag_index(4 * t + 7) << 11);
}
__device__ __forceinline__ void conv_zero(uint32_t cv, int t) {
  if (t < 115) sts128(cv + (t < 96 ? CV_ZERO + t * 16 : CV_IMG + IMG_P + (t < 100 ? t - 96 : t + 33) * 16), 0u, 0u, 0u, 0u);
}
__device__ __forceinline__ void conv_windows(uint32_t us, uint32_t rb, int t) {
  const uint32_t cv = rb - CV_R2;
  if (t >= 96) {
    if (t < 98) sts128(cv + CV_R2 + (t - 96) * 64, 0u, 0u, 0u, 0u);
    return;
  }
  uint32_t E[20];
  const uint32_t ua = us + (127 - t) * 16;
  const uint4 c0 = lds128(ua + U_PLANE + 32), c1 = lds128(ua + 16), c2 = lds128(ua + U_PLANE + 16), u0 = lds128(ua), u1 = lds128(ua + U_PLANE);
  E[0] = c0.x; E[1] = c0.y; E[2] = c0.z; E[3] = c0.w; E[4] = c1.x; E[5] = c1.y; E[6] = c1.z; E[7] = c1.w;
  E[8] = c2.x; E[9] = c2.y; E[10] = c2.z; E[11] = c2.w; E[12] = u0.x; E[13] = u0.y; E[14] = u0.z; E[15] = u0.w;
  E[16] = u1.x; E[17] = u1.y; E[18] = u1.z; E[19] = u1.w;
  uint32_t O[18], W2e[16], W4e[15], W5e[15], W2o[17], W3o[17];
#pragma unroll
  for (int k = 2; k < 18; k++) O[k] = __byte_perm(E[k], E[k + 1], 0x5432);
#pragma unroll
  for (int k = 7; k < 16; k++) W2e[k] = hadd2(E[k], O[k]);
#pragma unroll
  for (int k = 7; k < 15; k++) W4e[k] = hadd2(W2e[k], W2e[k + 1]);
#pragma unroll
  for (int k = 7; k < 15; k++) W5e[k] = hadd2(W4e[k], E[k + 2]);
#pragma unroll
  for (int k = 9; k < 17; k++) W2o[k] = hadd2(O[k], E[k + 1]);
#pragma unroll
  for (int k = 9; k < 17; k++) W3o[k] = hadd2(W2o[k], O[k + 1]);
  const int kg = t >> 2, c = 2 * (t & 3);
  {
    const uint32_t a = cv + CV_R2 + (kg >> 2) * 1296 + (c + 1) * 144 + (kg & 3) * 16;
    sts128(a, W3o[9], W3o[10], W3o[11], W3o[12]);
    sts128(a + 144, W3o[13], W3o[14], W3o[15], W3o[16]);
    sts128(a + 64, W5e[7], W5e[8], W5e[9], W5e[10]);
    sts128(a + 64 + 144, W5e[11], W5e[12], W5e[13], W5e[14]);
    if (c == 6 && kg < 23) {
      const uint32_t b = cv + CV_R2 + ((kg + 1) >> 2) * 1296 + ((kg + 1) & 3) * 16;
      sts128(b, W3o[13], W3o[14], W3o[15], W3o[16]);
      sts128(b + 64, W5e[11], W5e[12], W5e[13], W5e[14]);
    }
  }
  if (t < 64) {
    uint32_t W9[8], W7[8];
#pragma unroll
    for (int k = 2; k < 7; k++) W2e[k] = hadd2(E[k], O[k]);
#pragma unroll
    for (int k = 2; k < 7; k++) W4e[k] = hadd2(W2e[k], W2e[k + 1]);
#pragma unroll
    for (int k = 4; k < 7; k++) W5e[k] = hadd2(W4e[k], E[k + 2]);
#pragma unroll
    for (int k = 2; k < 10; k++) W9[k - 2] = hadd2(W4e[k], W5e[k + 2]);
#pragma unroll
    for (int k = 6; k < 9; k++) W2o[k] = hadd2(O[k], E[k + 1]);
    W3o[8] = hadd2(W2o[8], O[9]);
#pragma unroll
    for (int k = 6; k < 14; k++) W7[k - 6] = hadd2(hadd2(W2o[k], W2o[k + 1]), W3o[k + 2]);
    const uint32_t a = cv + CV_R3 + (kg >> 3) * 2304 + c * 144 + (kg & 7) * 16;
    sts128(a, W7[0], W7[1], W7[2], W7[3]);
    sts128(a + 144, W7[4], W7[5], W7[6], W7[7]);
    sts128(a + 1152, W9[0], W9[1], W9[2], W9[3]);
    sts128(a + 1152 + 144, W9[4], W9[5], W9[6], W9[7]);
  }
}
__device__ __forceinline__ constexpr int y_off(int w) { return 4160 * w - 64 + 8 * w * (w + 1); }
static_assert(CV_U + y_off(3) + 2112 + 2048 <= CV_SIZE, "y staging");
__device__ __forceinline__ void conv_finish(uint32_t y, int d, int t, int barid, bool direct) {
  const uint32_t a = y + (t & 1) * 2112 + (t >> 1) * 16;
  uint4 q[2][4];
#pragma unroll
  for (int r = 0; r < 2; r++) {
    q[r][0] = lds128(direct ? y + (t & 1) * 2048 + (((t >> 1) + r * 64) ^ ((t & 1) << 2)) * 16 : y + r * 2048 + t * 16);
#pragma unroll
    for (int ww = 1; ww < 4; ww++) q[r][ww] = lds128(a + r * 1024 + y_off(ww) - 16 * ww);
  }
#pragma unroll
  for (int r = 0; r < 2; r++) {
    const uint4 o = make_uint4(hadd2(hadd2(q[r][0].x, q[r][1].x), hadd2(q[r][2].x, q[r][3].x)), hadd2(hadd2(q[r][0].y, q[r][1].y), hadd2(q[r][2].y, q[r][3].y)),
                               hadd2(hadd2(q[r][0].z, q[r][1].z), hadd2(q[r][2].z, q[r][3].z)), hadd2(hadd2(q[r][0].w, q[r][1].w), hadd2(q[r][2].w, q[r][3].w)));
    if (direct) *reinterpret_cast<uint4*>(g_yT + (size_t)d * S_ + r * 1024 + t * 8) = o;
    else sts128(y + r * 2048 + t * 16, o.x, o.y, o.z, o.w);
  }
  if (!direct) fence_async_smem();
  named_bar(barid, 128);
  if (t == 0 && !direct) { bulk_store(g_yT + (size_t)d * S_, y, S_ * 2); bulk_commit(); }
}
__device__ __forceinline__ void conv_all(int chan0, int grp0, int c0, int n, int t, uint32_t cv, uint32_t us, uint32_t usl, uint32_t tab1,
                                         uint32_t yx, uint32_t bars, const uint32_t (&pix)[2], uint32_t hdr, uint32_t hdr1, int wg, int n0,
                                         int n1, int n2, int v) {
  const int lane = t & 31, w = t >> 5, barid = 1 + wg;
  const bool pre = chan0 >= 0;
  uint32_t ib = cv, rb = cv + CV_R2;
  int dprev = 0;
#pragma unroll 1
  for (int i = 0; i < n; i++) {
    if (pre && i == 1) named_bar(3 + 2 * wg, 256);
    uint32_t af[10][4];
    {
      const uint32_t a = ib + CV_IMG + IMG_P + (16 * w + (lane >> 2) - 2 * (lane & 3) + 16) * 4;
#pragma unroll
      for (int j = 0; j < 9; j++) {
        af[j][0] = lds32(a + j * 256); af[j][1] = lds32(a + j * 256 + 32); af[j][2] = lds32(a + j * 256 - 32);
      }
#pragma unroll
      for (int e = 0; e < 3; e++) {
        const int x = 16 * w + (lane >> 2) - 2 * (lane & 3) + (e == 0 ? -3 : e == 1 ? 5 : -11);
        af[9][e] = __byte_perm(hdr, 0, x == 0 ? 0x4410 : x == 1 ? 0x1010 : x == 2 ? 0x1044 : 0x4444);
      }
#pragma unroll
      for (int j = 0; j < 10; j++) af[j][3] = af[j][0] | (hdr >> 16);
    }
    named_bar(8 + wg, wg == 0 && i == 0 ? 128 : 256);
    TRP(t == 0, 16 + wg * 8 + 2 * i);
    asm volatile("{ .reg .pred p; setp.eq.b32 p, %0, 0; @p mbarrier.arrive.shared::cta.b64 _, [%1]; }" ::"r"(t + (wg ^ 1) + (n - 1 - i)),
                 "r"(bars + 8 * B_SYNC) : "memory");
    float z[64];
    {
      const uint32_t du = (us >> 4) | (U_PLANE >> 4 << 16), c4 = ib >> 4;
      const uint32_t dr2 = (rb >> 4) + (9 << 16), dr3 = (rb >> 4) + (((CV_R3 - CV_R2) >> 4) | (72 << 16));
      const uint32_t db2 = c4 + ((CV_ZERO >> 4) | (8 << 16)), db3 = c4 + (((CV_IMG + IMG_B3) >> 4) | (8 << 16));
      wg_fence();
      wg_dir128<8, 0>(z, af[0], du);
      wg_dir128<8, 1>(z, af[1], du + 4);
      wg_dir120<8, 1>(z, af[2], du + 8);
      wg_dir120<8, 1>(z, af[3], du + 12);
      wg_dir112<8, 1>(z, af[4], du + 16);
      wg_dir112<8, 1>(z, af[5], du + 20);
      wg_dir104<8, 1>(z, af[6], du + 24);
      wg_dir104<8, 1>(z, af[7], du + 28);
      wg_dir96<8, 1>(z, af[8], du + 32);
      wg_win96<9, 16>(z, dr2, db2);
      wg_win80<9, 16>(z, dr2 + 81, db2 + 32);
      wg_dir64<8, 1>(z, af[9], du + 64);
      wg_win64<9, 16>(z, dr2 + 2 * 81, db2 + 64);
      wg_win64<9, 16>(z, dr3, db3);
      wg_commit();
      wg_win48<9, 16>(z, dr2 + 3 * 81, db2 + 96);
      wg_win32<9, 16>(z, dr2 + 4 * 81, db2 + 128);
      wg_win32<9, 16>(z, dr3 + 144, db3 + 64);
      wg_win16<9, 16>(z, dr2 + 5 * 81, db2 + 160);
      wg_commit();
    }
    wg_wait<1>();
    TRP(t == 0 && pre, 44 + 2 * (wg - 1) + i);
    {
      const int nxt = wg == 0 ? (i < n1 ? 9 : 0) : wg == 1 ? (i < n2 ? 10 : 0) : n0 > 0 ? (i + 1 < n0 ? 8 : 0) : (i + 1 < n1 ? 9 : 0);
      asm volatile("{ .reg .pred p; setp.ne.b32 p, %0, 0; @p bar.arrive %0, 256; }" ::"r"(nxt) : "memory");
    }
    if (i > 0) {
      conv_finish(pre ? cv + CV_U : yx, dprev, t, barid, !pre);
      if (i + 1 == n && t == 0) {
        bulk_wait_read();
        mbar_arrive(bars + 8 * (!pre && wg > 0 ? B_BFREE : B_NONE));
        mbar_arrive(bars + 8 * B_STG);
      }
    }
    wg_wait<0>();
    named_bar(barid, 128);
    TRP(t == 0 && pre, 40 + 2 * (wg - 1) + i);
    const bool last = i + 1 == n, linear = pre || last;
    if (last && pre && t == 0) mbar_arrive(bars + 8 * (B_YFREE - 1 + wg));
    {
      const uint32_t y = linear ? cv + CV_U : yx;
      const int mat = lane >> 3, blk = 127 - 8 * (mat >> 1) - (lane & 7);
      const uint32_t a = y + (w > 0 ? y_off(w) + (mat & 1) * 2112 + blk * 16
                                    : linear ? blk * 32 + (mat & 1) * 16 : (mat & 1) * 2048 + (blk ^ ((mat & 1) << 2)) * 16);
      const uint32_t st = w == 0 && linear ? 512 : 256;
      if (w > 0 && lane < 2 * w) sts128(y + y_off(w) + (lane & 1) * 2112 - 16 - (lane >> 1) * 16, 0u, 0u, 0u, 0u);
#pragma unroll
      for (int g = 0; g < 8; g++)
        stsm4t(a - g * st, pk(z[8 * g], z[8 * g + 1]), pk(z[8 * g + 2], z[8 * g + 3]), pk(z[8 * g + 4], z[8 * g + 5]),
               pk(z[8 * g + 6], z[8 * g + 7]));
    }
    dprev = chan0 >= 0 ? chan0 + c0 + i : free_chan(grp0 + ((c0 + i) >> 2)) + ((c0 + i) & 3);
    if (!last && pre) { ib = yx; rb = yx + CV_U; us = usl; hdr = hdr1; }
    if (!last && !pre) {
      conv_image(tab1 + i * TB_SIZE, cv, t, pix);
      hdr = lds32(tab1 + i * TB_SIZE + TB_T + T_G1024 * 2);
      us = i + 2 == n ? usl : us + U_SIZE;
      conv_windows(us, cv + CV_R2, (t + 64 * (wg & 1) + 32 * (wg == 0)) & 127);
      fence_async_smem();
    }
    if (last || !pre) named_bar(barid, 128);
    TRP(t == 0, 16 + wg * 8 + 2 * i + 1);
  }
  conv_finish(cv + CV_U, dprev, t, barid, false);
}

__device__ __forceinline__ float ln_std(float var) {
  float sd;
  asm("sqrt.approx.f32 %0, %1;" : "=f"(sd) : "f"(bf16r(bf16r(var) + 1e-5f)));
  return bf16r(sd);
}
__device__ __forceinline__ float rcp(float x) { float r; asm("rcp.approx.f32 %0, %1;" : "=f"(r) : "f"(x)); return r; }
__device__ __forceinline__ void ln_block(int t256, uint32_t stage, uint32_t xch, uint32_t bars,
                                         const uint4* xr, int v) {
  const int lane = t256 & 31, w8 = t256 >> 5, rh = w8 & 1, cq = w8 >> 1, row = 8 * rh + (lane >> 2);
  float x[40];
#pragma unroll
  for (int i = 0; i < 5; i++) {
    x[8 * i + 0] = blo(xr[i].x); x[8 * i + 1] = bhi(xr[i].x); x[8 * i + 2] = blo(xr[i].y); x[8 * i + 3] = bhi(xr[i].y);
    x[8 * i + 4] = blo(xr[i].z); x[8 * i + 5] = bhi(xr[i].z); x[8 * i + 6] = blo(xr[i].w); x[8 * i + 7] = bhi(xr[i].w);
  }
  float s0 = 0.f, s1 = 0.f, q0 = 0.f, q1 = 0.f;
#pragma unroll
  for (int i = 0; i < 40; i += 2) { s0 += x[i]; s1 += x[i + 1]; q0 = fmaf(x[i], x[i], q0); q1 = fmaf(x[i + 1], x[i + 1], q1); }
  s0 += s1; q0 += q1;
  s0 += __shfl_xor_sync(~0u, s0, 1); q0 += __shfl_xor_sync(~0u, q0, 1);
  s0 += __shfl_xor_sync(~0u, s0, 2); q0 += __shfl_xor_sync(~0u, q0, 2);
  if ((lane & 3) == 0) asm volatile("st.shared.v2.f32 [%0], {%1,%2};" ::"r"(xch + row * 32 + cq * 8), "f"(s0), "f"(q0) : "memory");
  named_bar(4, 256);
  const uint4 e0 = lds128(xch + row * 32), e1 = lds128(xch + row * 32 + 16);
  const float mean = ((__uint_as_float(e0.x) + __uint_as_float(e0.z)) + (__uint_as_float(e1.x) + __uint_as_float(e1.z))) * (1.f / D_);
  const float msq = ((__uint_as_float(e0.y) + __uint_as_float(e0.w)) + (__uint_as_float(e1.y) + __uint_as_float(e1.w))) * (1.f / D_);
  const float var = fmaxf(msq - mean * mean, 0.f);
  const float m1 = bf16r(mean), r1 = rcp(ln_std(var));
  const float m2 = bf16r((mean - m1) * r1), sd2 = ln_std(var * r1 * r1), r2 = rcp(sd2);
  const float ca = 0.5f * r1 * r2, cb = -0.5f * (m1 * r1 + m2) * r2;
  const uint32_t a = stage + (160 * cq + lane) * 32 + ((rh ^ ((lane >> 2) & 1)) << 4);
#pragma unroll
  for (int i = 0; i < 5; i++)
    stsm4t(a + i * 1024, pk(fmaf(x[8 * i], ca, cb), fmaf(x[8 * i + 1], ca, cb)), pk(fmaf(x[8 * i + 2], ca, cb), fmaf(x[8 * i + 3], ca, cb)),
           pk(fmaf(x[8 * i + 4], ca, cb), fmaf(x[8 * i + 5], ca, cb)), pk(fmaf(x[8 * i + 6], ca, cb), fmaf(x[8 * i + 7], ca, cb)));
  if (cq == 0 && (lane & 3) == 0) {
    sts16(xch + 512 + row * 2, (uint16_t)(__float_as_uint(2.f * sd2) >> 16));
    sts16(xch + 544 + row * 2, (uint16_t)(__float_as_uint(m2) >> 16));
  }
  fence_async_smem();
  __syncwarp();
  if (lane == 0) mbar_arrive(bars + 8 * B_LNST);
}

template <bool G1>
__device__ __forceinline__ void gemm_loop(float* d, int& s, int& ph, uint32_t sb, uint32_t bars, int rel, int v) {
  constexpr uint32_t HA = 64 | (1u << 30), HB = G1 ? 16 | (3u << 30) : 64 | (1u << 30), BS = G1 ? 320 : 2;
  const bool leader = rel > 0;
  int prev = 0;
#pragma unroll 1
  for (int i = 0; i < (G1 ? KB1 : KB2); i++) {
    mbar_wait(bars + 8 * (B_FULL + s), ph);
    const uint32_t da = ((sb + SM_A) >> 4) + s * (SA >> 4) + (1 << 16), db = ((sb + SM_B) >> 4) + (G1 ? s : s < 3 ? s + 3 : s - 3) * (SB >> 4) + (1 << 16);
    wg_fence();
    wg_gemm160<HA, HB>(d, da, db, 1);
    wg_gemm160<HA, HB>(d, da + 128, db + BS, 1);
    wg_gemm160<HA, HB>(d, da + 256, db + 2 * BS, 1);
    wg_gemm160<HA, HB>(d, da + 384, db + 3 * BS, 1);
    wg_commit();
    wg_wait<1>();
    if (i > 0 && leader) mbar_arrive_n(bars + 8 * (B_EMPTY + prev), rel);
    prev = s;
    if (++s == STAGES) { s = 0; ph ^= 1; }
  }
  wg_wait<0>();
  if (leader) mbar_arrive_n(bars + 8 * (B_EMPTY + prev), rel);
}

__device__ __forceinline__ float gelu_half(float hu) {
  float th;
  asm("tanh.approx.f32 %0, %1;" : "=f"(th) : "f"(hu * fmaf(hu * hu, 8.f * 0.035677408136300125f, 2.f * 0.7978845608028654f)));
  return fmaf(hu, th, hu);
}

__device__ __forceinline__ void free_inputs(uint32_t sb, uint32_t bars, int grp0, int nch, int l1, int l2, int t) {
  mbar_wait(bars + 8 * B_UIN, 0);
  const int half = (t >> 4) & 1;
#pragma unroll 1
  for (int r = 0; r < 2; r++) {
    const int blk = r * 64 + (t >> 5) * 16 + (t & 15);
    const uint4 sd = lds128(sb + SM_FSD + blk * 32 + half * 16), mu = lds128(sb + SM_FSD + S_ * 2 + blk * 32 + half * 16);
    const uint32_t uo = half * U_PLANE + (127 - blk) * 16;
#pragma unroll 1
    for (int c4 = 0; c4 < nch; c4 += 4) {
      const uint32_t row = sb + SM_FST + c4 * 4096 + blk * 128, hp = (half ^ (free_chan(grp0 + (c4 >> 2)) >> 2)) & 1;
      uint32_t src[4], dst[4];
#pragma unroll
      for (int e = 0; e < 4; e++) {
        src[e] = row + (((2 * e + hp) ^ (blk & 7)) << 4);
        dst[e] = sb + (c4 + e == l1 ? SM_UX : c4 + e == l2 ? SM_UX + U_SIZE : SM_FU + (c4 + e) * U_SIZE) + uo;
      }
      conv_unnorm(src, dst, sd, mu);
    }
  }
  const int c = t >> 3;
  if (c < nch) sts128(sb + (c == l1 ? SM_UX : c == l2 ? SM_UX + U_SIZE : SM_FU + c * U_SIZE) + (t & 1) * U_PLANE + (128 + ((t >> 1) & 3)) * 16, 0u, 0u, 0u, 0u);
  __syncwarp();
  named_arrive(14, 512);
}

__device__ __forceinline__ void copy_inputs(uint32_t sb, uint32_t bars, int m1, int lane, int par) {
  const int c = lane >> 3, kq = (lane >> 1) & 3, half = lane & 1;
  const uint32_t src = sb + SM_B + kq * 5120 + (4 * m1 + c) * 32 + (((half ^ m1) & 1) << 4);
  uint32_t dst = conv_u(sb, c) + half * U_PLANE + (127 - 4 * par - kq) * 16;
  int s = par, ph = 0;
  bool all = false;
#pragma unroll 1
  for (int i = par; i < KB1; i += 2) {
    if (!all) {
      if ((i >> 1) == 11) mbar_wait(bars + 8 * B_KGDONE, 0);
      if (__all_sync(~0u, mbar_test(bars + 8 * B_KGDONE, 0))) {
        all = true;
        if (lane == 0) sts32(bars + 8 * B_WORD + 4 + 4 * par, i);
        __syncwarp();
        named_arrive(13, 320);
      }
    }
    mbar_wait(bars + 8 * (B_FULL + s), ph);
    const uint4 x = lds128(src + s * SB);
    if ((c & 1) || all) sts128(dst, x.x, x.y, x.z, x.w);
    __syncwarp();
    if (lane == 0) mbar_arrive(bars + 8 * (B_EMPTY + s));
    if ((i >> 1) == 11) named_arrive(11, 320);
    dst -= 128;
    s += 2;
    if (s >= STAGES) { s -= STAGES; ph ^= 1; }
  }
  named_arrive(15, 128);
}

__global__ void __launch_bounds__(NTHREADS, 1)
fused_kernel(const __grid_constant__ CUtensorMap m_w1, const __grid_constant__ CUtensorMap m_w2, const __grid_constant__ CUtensorMap m_hT,
             const __grid_constant__ CUtensorMap m_G, const __grid_constant__ CUtensorMap m_hu, const __grid_constant__ CUtensorMap m_yT,
             const Params p) {
  extern __shared__ __align__(1024) unsigned char smem_raw[];
  const int tid = threadIdx.x;
  uint4 xr[5];
  unsigned smid;
  asm volatile("mov.u32 %0, %%smid;" : "=r"(smid));
  const int vv = p.use_smid ? (int)smid : (int)blockIdx.x;
  const int lnblk = (p.dbg & 64) ? (int)blockIdx.x : vv < 120 ? vv : vv < 124 ? 128 : vv - 4;
  const bool do_ln = (p.phases & 1) && lnblk < 128;
  if (do_ln && tid >= 128 && tid < 384) {
    const int w8 = (tid - 128) >> 5;
    const __nv_bfloat16* src = p.x + (size_t)(lnblk * 16 + 8 * (w8 & 1) + ((tid & 31) >> 2)) * D_ + 160 * (w8 >> 1) + (tid & 3) * 8;
#pragma unroll
    for (int i = 0; i < 5; i++) xr[i] = __ldg(reinterpret_cast<const uint4*>(src + i * 32));
  }
  if (tid < 60 && lnblk < 128 && (p.phases & 2) && !(p.dbg & 1024)) {
    const int arr = tid / 10;
    const __nv_bfloat16* base = arr == 0 ? p.are : arr == 1 ? p.aim : arr == 2 ? p.bre : arr == 3 ? p.bim : arr == 4 ? p.cre : p.cim;
    asm volatile("prefetch.global.L2 [%0];" ::"l"(base + lnblk * 640 + (tid % 10) * 64));
  }
  const uint32_t sb = __shfl_sync(~0u, smem_u32(smem_raw), 0);
  const uint32_t bars = sb + SM_BAR;
  const int wid = __shfl_sync(~0u, tid >> 5, 0);
  unsigned* cnt = g_cnt;

  const int v = __shfl_sync(~0u, vv, 0);
  int g, pos;
  if (v < 64) { g = (v >> 1) & 7; pos = (v >> 4) * 2 + (v & 1); }
  else if (v < 120) { const int tt = (v - 64) >> 1; g = 1 + tt % 7; pos = 8 + (tt / 7) * 2 + (v & 1); }
  else if (v < 124) { g = 6 + ((v - 120) >> 1); pos = 16 + (v & 1); }
  else { g = 0; pos = 8 + (v - 124); }
  const int e2 = pos & 1, j = (pos >> 1) & 3;
  const int m2 = pos < 16 ? g * 4 + e2 + 2 * (pos >> 3) : -1;
  const int q = e2 + 2 * (pos >> 3);
  const int m1 = pos < 16 && (q < 3 || g < 3) ? (g < 3 ? 4 * g : 3 * g + 3) + q : -1;
  const bool ph_b = p.phases & 2, ph_c = p.phases & 4, fused = p.phases == 7;
  const bool do_g1 = ph_b && m1 >= 0, do_g2 = ph_c && m2 >= 0, do_cv = ph_b && !(p.dbg & 1);
  const int wg = wid >> 2, chan0 = m1 >= 0 ? 160 * j + 4 * m1 : -1;
  const int grp0 = pos < 16 ? ((g - 3) * 4 + j) * 2 : 40 + ((g - 6) * 2 + e2) * 3;
  const int nch = m1 >= 0 ? 4 : pos < 16 ? 8 : 12;
  const int n0 = m1 >= 0 ? 0 : (nch + 2) / 3, n1 = (nch - n0 + 1) >> 1, n2 = nch - n0 - n1;
  const int c0 = wg == 0 ? 0 : wg == 1 ? n0 : n0 + n1, cn = wg == 0 ? n0 : wg == 1 ? n1 : n2;
  const bool ksplit = nch < 12;
  const int kc = !ksplit ? wid : wid >= 4 ? nch - 4 + (wid & 3) : wid;
  KgIn kin;
  if (wid < 12 && (wid >= 4 || m1 < 0) && do_cv) kin = kg_load(p, m1 >= 0 ? chan0 + kc : free_chan(grp0 + (kc >> 2)) + (kc & 3), tid & 31);
  if (tid == 0) {
    if (sb & 1023) __trap();
    for (int s = 0; s < STAGES; s++) { mbar_init(bars + 8 * (B_FULL + s), 2); mbar_init(bars + 8 * (B_EMPTY + s), 2); }
    mbar_init(bars + 8 * B_LNDONE, 1); mbar_init(bars + 8 * B_EPIY, 1); mbar_init(bars + 8 * B_CVFREE, m1 >= 0 ? 2 : 3);
    mbar_init(bars + 8 * B_EPOCH, 1); mbar_init(bars + 8 * B_LNST, 8); mbar_init(bars + 8 * B_GST, 4);
    mbar_init(bars + 8 * B_UIN, 1); mbar_init(bars + 8 * B_BFREE, 3); mbar_init(bars + 8 * B_NONE, 8); mbar_init(bars + 8 * B_KGDONE, 1);
    mbar_init(bars + 8 * B_STG, 3); mbar_init(bars + 8 * B_SYNC, 1); mbar_init(bars + 8 * B_KGMMA, 8); mbar_init(bars + 8 * B_YOK, 1);
    mbar_init(bars + 8 * B_YFREE, 1); mbar_init(bars + 8 * (B_YFREE + 1), 1);
    for (int s = 0; s < 3; s++) mbar_init(bars + 8 * (B_LNG + s), 1);
    asm volatile("fence.mbarrier_init.release.cluster;" ::: "memory");
    fence_async_smem();
  }
  __syncthreads();

  if (wid >= 12) {
    asm volatile("setmaxnreg.dec.sync.aligned.u32 56;");
    if (wid < 14) {
     unsigned ep = 0;
     if (fused && wid == 13) {
       asm volatile("ld.relaxed.gpu.global.u32 %0, [%1];" : "=r"(ep) : "l"(cnt + C_EPOCH) : "memory");
       ep += 1;
       if (elect()) { sts32(bars + 8 * B_WORD, ep); mbar_arrive(bars + 8 * B_EPOCH); }
     }
     if (do_cv && m1 < 0) free_inputs(sb, bars, grp0, nch, n0 + n1 - 1, nch - 1, tid & 127);
     if (wid == 12) {
      int s = 0, ph = 1;
      if (do_g1) {
#pragma unroll 1
        for (int i = 0; i < KB1; i++) {
          mbar_wait(bars + 8 * (B_EMPTY + s), ph);
          if (elect()) {
            mbar_expect_tx(bars + 8 * (B_FULL + s), SA);
            tma_load(sb + SM_A + s * SA, &m_w1, m1 * 64, i * 64, bars + 8 * (B_FULL + s));
            if (i + STAGES < KB1 && ((i + STAGES) & 3) == j) tma_prefetch(&m_w1, m1 * 64, (i + STAGES) * 64);
            if (do_g2 && i >= 5 && ((i - 5) & 3) == j) tma_prefetch(&m_w2, m2 * 64, (i - 5) * 64);
          }
          if (++s == STAGES) { s = 0; ph ^= 1; }
        }
      } else if (m1 < 0 && do_g2) {
        if (fused) mbar_wait(bars + 8 * B_LNALL, 0);
        for (int k = j; k < KB2; k += 4)
          if (elect()) tma_prefetch(&m_w2, m2 * 64, k * 64);
        mbar_wait(bars + 8 * B_BFREE, 0);
      }
      if (do_g2) {
#pragma unroll 1
        for (int i = 0; i < KB2; i++) {
          mbar_wait(bars + 8 * (B_EMPTY + s), ph);
          if (elect()) {
            mbar_expect_tx(bars + 8 * (B_FULL + s), SA);
            tma_load(sb + SM_A + s * SA, &m_w2, m2 * 64, i * 64, bars + 8 * (B_FULL + s));
          }
          if (++s == STAGES) { s = 0; ph ^= 1; }
        }
      }
     } else {
      int s = 0, ph = 1;
      if (do_g1) {
        if (fused) cnt_wait_timed(cnt + C_LN, ep * N_LN);
        TRP(tid == 13 * 32, 2);
#pragma unroll 1
        for (int i = 0; i < KB1; i++) {
          if (fused && (i & 7) == 0 && i > 0) mbar_wait(bars + 8 * (B_LNG - 1 + (i >> 3)), 0);
          mbar_wait(bars + 8 * (i == 4 ? B_LNDONE : B_EMPTY + s), i == 4 ? 0 : ph);
          if (elect()) {
            mbar_expect_tx(bars + 8 * (B_FULL + s), SB);
            tma_load3(sb + SM_B + s * SB, &m_hT, 0, j * 40, i * 4, bars + 8 * (B_FULL + s));
          }
          if (++s == STAGES) { s = 0; ph ^= 1; }
        }
      }
      if (do_g2) {
        if (do_g1) for (int k = 0; k < STAGES; k++) mbar_wait(bars + 8 * (B_EMPTY + k), k < KB1 % STAGES);
        if (fused) cnt_wait_timed(cnt + C_G, ep * N_G);
        TRP(tid == 13 * 32, 7);
        if (m1 < 0) mbar_wait(bars + 8 * B_BFREE, 0);
#pragma unroll 1
        for (int i = 0; i < KB2; i++) {
          if ((i >> 1) == 2 && do_g1 && do_cv) mbar_wait(bars + 8 * (B_YFREE - 4 + i), 0);
          mbar_wait(bars + 8 * (B_EMPTY + s), ph);
          if (elect()) {
            mbar_expect_tx(bars + 8 * (B_FULL + s), SB);
            tma_load(sb + SM_B + (s < 3 ? s + 3 : s - 3) * SB, &m_G, i * 64, j * 160, bars + 8 * (B_FULL + s));
          }
          if (++s == STAGES) { s = 0; ph ^= 1; }
        }
        mbar_wait(bars + 8 * B_YOK, 0);
        if (elect()) {
          mbar_expect_tx(bars + 8 * B_EPIY, 20480);
          tma_load(sb + SM_CV, &m_yT, m2 * 64, j * 160, bars + 8 * B_EPIY);
        }
        TRP(tid == 13 * 32, 51);
      }
     }
    } else {
      const int lane = tid & 31;
      if (tid == 15 * 32) {
        if (do_ln) {
          mbar_wait(bars + 8 * B_LNST, 0);
          bulk_store(g_hT + (size_t)lnblk * (D_ * 16), sb + SM_LNST, D_ * 32);
          bulk_store(g_st + lnblk * 16, sb + SM_LNX + 512, 32);
          bulk_store(g_st + S_ + lnblk * 16, sb + SM_LNX + 544, 32);
          bulk_commit();
          bulk_wait_all();
          if (fused) cnt_arrive_timed(cnt + C_LN + (lnblk & ~31), p.uat2);
        }
        mbar_arrive(bars + 8 * B_LNDONE);
      } else if (tid == 14 * 32) {
        if (fused) {
          mbar_wait(bars + 8 * B_EPOCH, 0);
          const unsigned tg = lds32(bars + 8 * B_WORD) * N_LN;
          if (do_ln) mbar_wait(bars + 8 * B_LNST, 0);
          unsigned seen = 0;
#pragma unroll 1
          for (int it = 0; seen < 3; it++) {
            unsigned c[4];
#pragma unroll
            for (int k = 0; k < 4; k++) asm volatile("ld.relaxed.gpu.global.u32 %0, [%1];" : "=r"(c[k]) : "l"(cnt + C_LN + 32 * k) : "memory");
            if (seen == 0 && (int)(c[1] - tg) >= 0) { mbar_arrive(bars + 8 * B_LNG); seen = 1; }
            if (seen == 1 && (int)(c[2] - tg) >= 0) { mbar_arrive(bars + 8 * (B_LNG + 1)); seen = 2; }
            if (seen == 2 && (int)(c[3] - tg) >= 0 && (int)(c[0] - tg) >= 0) { mbar_arrive(bars + 8 * B_LNALL); seen = 3; }
            if (it > (1 << 20)) __trap();
          }
          TR(15);
        }
        if (do_cv && m1 < 0) {
          mbar_expect_tx(bars + 8 * B_UIN, nch * 4096 + S_ * 4);
          bulk_load(sb + SM_FSD, g_st, S_ * 4, bars + 8 * B_UIN);
          for (int c4 = 0; c4 < nch; c4 += 4) {
            tma_load(sb + SM_FST + c4 * 4096, &m_hu, free_chan(grp0 + (c4 >> 2)) * 16, 0, bars + 8 * B_UIN);
            tma_load(sb + SM_FST + c4 * 4096 + 8192, &m_hu, free_chan(grp0 + (c4 >> 2)) * 16, 64, bars + 8 * B_UIN);
          }
        }
      }
      __syncwarp();
      if (do_cv) {
        if (m1 >= 0) copy_inputs(sb, bars, m1, lane, 15 - wid);
        else free_inputs(sb, bars, grp0, nch, n0 + n1 - 1, nch - 1, tid & 127);
      }
      if (tid == 15 * 32) {
        if (do_g1) {
          mbar_wait(bars + 8 * B_GST, 0);
          tma_store(&m_G, m1 * 64, j * 160, sb + SM_B + (KB1 % STAGES) * SB);
          bulk_commit();
          bulk_wait_all();
          TR(6);
        }
        if (fused && m2 >= 0) {
          if (do_cv && !(p.dbg & 512)) mbar_wait(bars + 8 * (m1 >= 0 ? B_SYNC : B_BFREE), 0);
          cnt_arrive_timed(cnt + C_G, p.uat);
        }
      } else if (tid == 14 * 32) {
        if (fused && do_cv && m1 < 0) {
          mbar_wait(bars + 8 * B_STG, 0);
          if (p.dbg & 128) fence_async_all();
          asm volatile("fence.acq_rel.gpu;" ::: "memory");
          TR(52);
        }
        mbar_wait(bars + 8 * B_CVFREE, 0);
        if (fused) {
          TR(50);
          const unsigned ep = lds32(bars + 8 * B_WORD);
          cnt_arrive_done(cnt + C_CONV);
          if (do_g2) cnt_wait(cnt + C_CONV, ep * NCTA);
          if (v == 0) asm volatile("st.relaxed.gpu.global.u32 [%0], %1;" ::"l"(cnt + C_EPOCH), "r"(ep) : "memory");
        }
        TR(8);
        mbar_arrive(bars + 8 * B_YOK);
      }
    }
  } else {
    asm volatile("setmaxnreg.inc.sync.aligned.u32 152;");
    const int t = tid & 127, lane = t & 31, w = wid & 3;
    int s = 0, ph = 0;
    if (do_ln && wg > 0) ln_block(tid - 128, sb + SM_LNST, sb + SM_LNX, bars, xr, v);
    TRP(tid == 128, 1);
    const uint32_t cv = wg > 0 ? sb + SM_CV + (wg - 1) * CV_SIZE : sb + SM_A;
    if (wg == 0 && m1 >= 0) {
      if (do_g1) {
        float d[80];
        const float bias0 = 0.5f * ldbf(p.b1 + m1 * 64 + 16 * w + (lane >> 2)), bias1 = 0.5f * ldbf(p.b1 + m1 * 64 + 16 * w + 8 + (lane >> 2));
#pragma unroll
        for (int i = 0; i < 80; i++) d[i] = (i & 2) ? bias1 : bias0;
        if (do_cv) mbar_wait(bars + 8 * B_KGMMA, 0);
        gemm_loop<true>(d, s, ph, sb, bars, t == 0 ? (do_cv ? 1 : 2) : 0, v);
        if (do_cv && (p.dbg & 256)) asm volatile("bar.arrive 9, 256;" : "+f"(d[0]), "+f"(d[1]), "+f"(d[2]), "+f"(d[3])::"memory");
        mbar_wait(bars + 8 * (B_EMPTY + KB1 % STAGES), (KB1 / STAGES - 1) & 1);
        const int mat = lane >> 3, rho = lane & 7;
        const uint32_t a = sb + SM_B + (KB1 % STAGES) * SB + (8 * (mat >> 1) + rho) * 128 + (((2 * w + (mat & 1)) ^ rho) << 4);
#pragma unroll
        for (int i = 0; i < 10; i++) {
          const float* e = d + 8 * i;
          stsm4t(a + i * 2048, pk(gelu_half(e[0]), gelu_half(e[1])), pk(gelu_half(e[2]), gelu_half(e[3])), pk(gelu_half(e[4]), gelu_half(e[5])),
                 pk(gelu_half(e[6]), gelu_half(e[7])));
        }
        fence_async_smem();
        __syncwarp();
        if (lane == 0) mbar_arrive(bars + 8 * B_GST);
        if (do_cv && !(p.dbg & 256)) named_arrive(9, 256);
        TRP(t == 0, 5);
        if (do_cv) {
          uint32_t pix[2];
          conv_pix(pix, t);
          named_bar(12, 384);
#pragma unroll 1
          for (int k = 0; k < 2; k++) {
            const uint32_t op = sb + SM_B + (3 + k) * SB;
            conv_image(sb + SM_TABX + k * TB_SIZE, op, t, pix);
            conv_zero(op, t);
            conv_windows(sb + SM_UX + k * U_SIZE, op + CV_U, (t + 64 * k) & 127);
            fence_async_smem();
            named_arrive(5 + 2 * k, 256);
            TRP(t == 0, 58 + k);
          }
        }
      }
    } else {
      if (do_cv) {
        if (wg == 0 && do_ln) mbar_wait(bars + 8 * B_LNST, 0);
        kgen_channel(kin, lane, cv + w * 32 * KG_REC,
                     m1 < 0 ? sb + SM_FTAB + kc * TB_SIZE
                            : (kc & 1) ? sb + SM_TABX + (kc >> 1) * TB_SIZE : sb + SM_CV + (kc >> 1) * CV_SIZE + CV_TAB,
                     ksplit && wg == 2 ? 2 : 0, ksplit && wg == 1 ? 2 : 4, sb + SM_CV + CV_SIZE + w * 32 * KG_REC,
                     ksplit && wg > 0 ? bars + 8 * B_KGMMA : 0);
        TRP(t == 0 && m1 >= 0, 9 + wg);
        uint32_t pix[2];
        conv_pix(pix, t);
        const int t256 = tid - 128, blk = (t256 >> 5) * 16 + (t256 & 15), half = (t256 >> 4) & 1;
        const uint32_t uo = half * U_PLANE + (127 - blk) * 16;
        uint4 sd, mu;
        if (m1 >= 0) {
          if (fused) mbar_wait(bars + 8 * B_LNALL, 0);
          sd = ldg128(g_st + blk * 16 + half * 8); mu = ldg128(g_st + S_ + blk * 16 + half * 8);
        }
        named_bar(14, m1 >= 0 ? 256 : 512);
        if (tid == 128) mbar_arrive(bars + 8 * B_KGDONE);
        const uint32_t tab0 = m1 >= 0 ? cv + CV_TAB : sb + SM_FTAB + c0 * TB_SIZE, us0 = m1 >= 0 ? cv + CV_U : sb + SM_FU + c0 * U_SIZE;
        if (m1 < 0 && wg > 0) named_bar(4 + wg, 256);
        conv_image(tab0, cv, t, pix);
        const uint32_t hdr = lds32(tab0 + TB_T + T_G1024 * 2);
        conv_zero(cv, t);
        const uint32_t usl = wg > 0 ? sb + SM_UX + (wg - 1) * U_SIZE : us0 + (cn - 1) * U_SIZE;
        const uint32_t tab1 = m1 >= 0 ? sb + SM_TABX + (wg - 1) * TB_SIZE : tab0 + TB_SIZE;
        const uint32_t op1 = m1 >= 0 ? sb + SM_B + (2 + wg) * SB : sb + SM_FST + wg * 16768;
        uint32_t hdr1 = 0;
        uint32_t ua[4];
#pragma unroll
        for (int e = 0; e < 4; e++) ua[e] = conv_u(sb, e) + uo;
        if (m1 >= 0) {
          if (t256 >= 224) sts128(conv_u(sb, (t256 >> 3) & 3) + (t256 & 1) * U_PLANE + (128 + ((t256 >> 1) & 3)) * 16, 0u, 0u, 0u, 0u);
          named_bar(13, 320);
          if ((blk >> 2) < (int)lds32(bars + 8 * B_WORD + 4 + (blk & 4))) {
            const __nv_bfloat16* src = g_hT + (size_t)blk * (D_ * 16) + chan0 * 16 + ((half ^ m1) & 1) * 8;
            const uint4 x0 = ldg128(src), x2 = ldg128(src + 32);
            sts128(ua[0], x0.x, x0.y, x0.z, x0.w);
            sts128(ua[2], x2.x, x2.y, x2.z, x2.w);
          }
          named_bar(11, 320);
          if (blk < 96) conv_unnorm(ua, ua, sd, mu);
        }
        TRP(tid == 128, 49);
        named_bar(m1 >= 0 ? 4 : 1 + wg, m1 >= 0 ? 256 : 128);
        conv_windows(us0, cv + CV_R2, (t + 64 * (wg & 1) + 32 * (wg == 0)) & 127);
        if (m1 >= 0) {
          if (blk >= 96) {
            named_bar(15, 128);
            conv_unnorm(ua, ua, sd, mu);
          }
          hdr1 = lds32(tab1 + TB_T + T_G1024 * 2);
          fence_async_smem();
          named_bar(4, 256);
          named_arrive(12, 384);
          TRP(t == 0, 52 + wg);
        } else {
          fence_async_smem();
          if (wg < 2) named_arrive(5 + wg, 256);
        }
        conv_all(chan0, grp0, c0, cn, t, cv, us0, usl, tab1, op1, bars, pix, hdr, hdr1, wg, n0, n1, n2, v);
      }
      if (t == 0) {
        bulk_wait_all();
        mbar_arrive(bars + 8 * (wg == 0 || !do_cv ? B_BFREE : B_NONE));
        mbar_arrive(bars + 8 * B_CVFREE);
      }
    }
    if (wg == 0 && do_g2) {
      float d[80];
      const int row = m2 * 64 + 16 * w + (lane >> 2);
      const size_t off = (size_t)row * D_ + j * 160 + (lane & 3) * 8;
      {
        uint4 xv[10];
#pragma unroll
        for (int i = 0; i < 10; i++) xv[i] = __ldg(reinterpret_cast<const uint4*>(p.x + off + (i & 1) * 8 * D_ + (i >> 1) * 32));
        const float bias0 = ldbf(p.b2 + row), bias1 = ldbf(p.b2 + row + 8);
#pragma unroll
        for (int i = 0; i < 10; i++) {
          float* e = d + 16 * (i >> 1) + 2 * (i & 1);
          const float bias = (i & 1) ? bias1 : bias0;
          e[0] = blo(xv[i].x) + bias; e[1] = bhi(xv[i].x) + bias; e[4] = blo(xv[i].y) + bias; e[5] = bhi(xv[i].y) + bias;
          e[8] = blo(xv[i].z) + bias; e[9] = bhi(xv[i].z) + bias; e[12] = blo(xv[i].w) + bias; e[13] = bhi(xv[i].w) + bias;
        }
      }
      gemm_loop<false>(d, s, ph, sb, bars, t == 0 ? 2 : 0, v);
      TRP(t == 0, 12);
      mbar_wait(bars + 8 * B_EPIY, 0);
      const uint32_t ay = sb + SM_CV + lane * 128;
#pragma unroll
      for (int i = 0; i < 10; i++) {
        uint32_t y[4];
        ldsm4t(y, ay + (i >> 1) * 4096 + (((2 * w + (i & 1)) ^ (lane & 7)) << 4));
        const float* e = d + 16 * (i >> 1) + 2 * (i & 1);
        *reinterpret_cast<uint4*>(p.out + off + (i & 1) * 8 * D_ + (i >> 1) * 32) =
            make_uint4(pk(e[0] + blo(y[0]), e[1] + bhi(y[0])), pk(e[4] + blo(y[1]), e[5] + bhi(y[1])), pk(e[8] + blo(y[2]), e[9] + bhi(y[2])),
                       pk(e[12] + blo(y[3]), e[13] + bhi(y[3])));
      }
      TRP(t == 0, 13);
    }
  }
}

typedef CUresult (*EncodeFn)(CUtensorMap*, CUtensorMapDataType, cuuint32_t, void*, const cuuint64_t*, const cuuint64_t*, const cuuint32_t*,
                             const cuuint32_t*, CUtensorMapInterleave, CUtensorMapSwizzle, CUtensorMapL2promotion, CUtensorMapFloatOOBfill);

CUtensorMap make_map(EncodeFn enc, const void* ptr, uint64_t inner, uint64_t outer, uint32_t bi, uint32_t bo, CUtensorMapSwizzle sw) {
  CUtensorMap m;
  cuuint64_t dims[2] = {inner, outer}, strides[1] = {inner * 2};
  cuuint32_t box[2] = {bi, bo}, es[2] = {1, 1};
  enc(&m, CU_TENSOR_MAP_DATA_TYPE_BFLOAT16, 2, const_cast<void*>(ptr), dims, strides, box, es, CU_TENSOR_MAP_INTERLEAVE_NONE, sw,
      CU_TENSOR_MAP_L2_PROMOTION_L2_128B, CU_TENSOR_MAP_FLOAT_OOB_FILL_NONE);
  return m;
}

}

#define FORCE_PHASED 0

extern "C" void kernel_launch(void* const* d_in, const int* in_sizes, int n_in, void* d_out, int out_size) {
  typedef const __nv_bfloat16* bp;
  void* fn = nullptr;
  cudaDriverEntryPointQueryResult st;
  cudaGetDriverEntryPoint("cuTensorMapEncodeTiled", &fn, cudaEnableDefault, &st);
  EncodeFn enc = (EncodeFn)fn;
  void *hT, *G, *yT;
  cudaGetSymbolAddress(&hT, g_hT); cudaGetSymbolAddress(&G, g_G); cudaGetSymbolAddress(&yT, g_yT);
  const CUtensorMap m_w1 = make_map(enc, d_in[10], F_, S_, 64, 64, CU_TENSOR_MAP_SWIZZLE_128B);
  const CUtensorMap m_w2 = make_map(enc, d_in[12], S_, F_, 64, 64, CU_TENSOR_MAP_SWIZZLE_128B);
  CUtensorMap m_hT;
  {
    cuuint64_t dims[3] = {64, D_ / 4, S_ / 16}, strides[2] = {128, D_ * 32};
    cuuint32_t box[3] = {64, 40, 4}, es[3] = {1, 1, 1};
    enc(&m_hT, CU_TENSOR_MAP_DATA_TYPE_BFLOAT16, 3, hT, dims, strides, box, es, CU_TENSOR_MAP_INTERLEAVE_NONE, CU_TENSOR_MAP_SWIZZLE_NONE,
        CU_TENSOR_MAP_L2_PROMOTION_L2_128B, CU_TENSOR_MAP_FLOAT_OOB_FILL_NONE);
  }
  const CUtensorMap m_G = make_map(enc, G, F_, D_, 64, 160, CU_TENSOR_MAP_SWIZZLE_128B);
  const CUtensorMap m_yT = make_map(enc, yT, S_, D_, 64, 160, CU_TENSOR_MAP_SWIZZLE_128B);
  const CUtensorMap m_hu = make_map(enc, hT, D_ * 16, S_ / 16, 64, 64, CU_TENSOR_MAP_SWIZZLE_128B);
  Params p;
  p.dbg = 0; p.uat = 0; p.uat2 = 0;
  p.out = (__nv_bfloat16*)d_out; p.x = (bp)d_in[0]; p.are = (bp)d_in[1]; p.aim = (bp)d_in[2]; p.bre = (bp)d_in[3]; p.bim = (bp)d_in[4]; p.cre = (bp)d_in[5];
  p.cim = (bp)d_in[6]; p.logdt = (bp)d_in[7]; p.dskip = (bp)d_in[8]; p.b1 = (bp)d_in[11]; p.b2 = (bp)d_in[13];
  cudaFuncSetAttribute(fused_kernel, cudaFuncAttributeMaxDynamicSharedMemorySize, SMEM_BYTES);
  int dev = 0, sms = 0;
  cudaGetDevice(&dev);
  cudaDeviceGetAttribute(&sms, cudaDevAttrMultiProcessorCount, dev);
  if (sms >= NCTA && !FORCE_PHASED) {
    p.phases = 7; p.use_smid = (sms == NCTA) && !(p.dbg & 16);
    fused_kernel<<<NCTA, NTHREADS, SMEM_BYTES>>>(m_w1, m_w2, m_hT, m_G, m_hu, m_yT, p);
  } else {
    p.use_smid = 0;
    for (int ph = 1; ph <= 4; ph <<= 1) {
      p.phases = ph;
      fused_kernel<<<NCTA, NTHREADS, SMEM_BYTES>>>(m_w1, m_w2, m_hT, m_G, m_hu, m_yT, p);
    }
  }
}
```
